```python
import torch

def _softmax(x, axis=-1):
    return torch.softmax(x, dim=axis)
def _gelu(x):
    return torch.nn.functional.gelu(x, approximate="tanh")
def _silu(x):
    return torch.nn.functional.silu(x)
def _sigmoid(x):
    return torch.sigmoid(x)
def _layernorm(x, axis=-1, eps=1e-5):
    m = x.mean(dim=axis, keepdim=True)
    v = x.var(dim=axis, keepdim=True, unbiased=False)
    return (x - m) / torch.sqrt(v + eps)
def _scatter_add(tgt, idx, src, axis=0):
    return tgt.clone().index_add_(axis, idx, src)
def _segment_sum(src, seg, n):
    out = torch.zeros((n,) + src.shape[1:], dtype=src.dtype)
    return out.index_add_(0, seg, src)
def _pad(x, pw):
    flat = tuple(v for pair in reversed(pw) for v in pair)
    return torch.nn.functional.pad(x, flat)

kernel_name = 'interleave_layers__sliding_local_dilated__mixer_token_mlp__prompt'

def setup_inputs():

    _w = (lambda a: (lambda t: t.to(torch.bfloat16) if t.is_floating_point() else t)(torch.as_tensor(a)))
    def _A_setup():
        B, S, D = 1, 2048, 1024
        return {
            "x": _w((lambda *s: torch.randn(*s, dtype=torch.bfloat16) * 0.05)(B, S, D)),
            "wqkv": _w((lambda *s: torch.randn(*s, dtype=torch.bfloat16) * 0.05)(D, 3 * D)),
            "wo": _w((lambda *s: torch.randn(*s, dtype=torch.bfloat16) * 0.05)(D, D)),
        }
    _A_in = _A_setup()

    def _B_setup():
        B, S, D, F = 1, 2048, 1024, 3584
        return {
            "x": _w((lambda *s: torch.randn(*s, dtype=torch.bfloat16) * 0.05)(B, S, D)),
            "w1": _w((lambda *s: torch.randn(*s, dtype=torch.bfloat16) * 1.6)(S, F) * (S ** -0.5)),
            "b1": _w((lambda *s: torch.randn(*s, dtype=torch.bfloat16) * 1.6)(F) * 0.02),
            "w2": _w((lambda *s: torch.randn(*s, dtype=torch.bfloat16) * 1.6)(F, S) * (F ** -0.5)),
            "b2": _w((lambda *s: torch.randn(*s, dtype=torch.bfloat16) * 1.6)(S) * 0.02),
        }
    _B_in = _B_setup()

    return {
        "A_x": _A_in["x"],
        "A_wqkv": _A_in["wqkv"],
        "A_wo": _A_in["wo"],
        "B_x": _B_in["x"],
        "B_w1": _B_in["w1"],
        "B_b1": _B_in["b1"],
        "B_w2": _B_in["w2"],
        "B_b2": _B_in["b2"],
    }

def reference(A_x, A_wqkv, A_wo, B_x, B_w1, B_b1, B_w2, B_b2):
    def _A_ref(x, wqkv, wo):
        B, S, D = x.shape
        H = 32; Dh = D // H
        W, dil = 8, 2
        qkv = (lambda x, *d: x.permute(*d))((x @ wqkv).reshape(B, S, 3, H, Dh), 2, 0, 3, 1, 4)
        q, k, v = qkv[0], qkv[1], qkv[2]
        scale = Dh ** -0.5
        pos = torch.arange(S)
        off = torch.arange(W) * dil
        idx = pos[:, None] - off[None, :]
        mask = idx >= 0
        idx_c = torch.where(mask, idx, 0).reshape(-1)
        kg = k[:, :, idx_c, :].reshape(B, H, S, W, Dh)
        vg = v[:, :, idx_c, :].reshape(B, H, S, W, Dh)
        logits = torch.einsum("bhsd,bhswd->bhsw", q, kg) * scale
        logits = torch.where(mask[None, None, :, :], logits, -1e9)
        attn = _softmax(logits, axis=-1)
        o = torch.einsum("bhsw,bhswd->bhsd", attn, vg)
        return (lambda x, *d: x.permute(*d))(o, 0, 2, 1, 3).reshape(B, S, D) @ wo

    def _B_ref(x, w1, b1, w2, b2):
        B, S, D = x.shape
        h = _layernorm(x, axis=-1)
        u = torch.einsum("bsd,sf->bdf", h, w1) + b1
        u = _gelu(u)
        y = torch.einsum("bdf,fs->bds", u, w2) + b2
        return (lambda x, *d: x.permute(*d))(y, 0, 2, 1)

    x = A_x
    x = x + _A_ref(_layernorm(x, axis=-1), A_wqkv, A_wo)
    x = x + _B_ref(_layernorm(x, axis=-1), B_w1, B_b1, B_w2, B_b2)
    x = x + _A_ref(_layernorm(x, axis=-1), A_wqkv, A_wo)
    x = x + _B_ref(_layernorm(x, axis=-1), B_w1, B_b1, B_w2, B_b2)
    return x
```

```cpp
#include <cuda_runtime.h>
#include <cuda_bf16.h>
#include <cuda.h>
#include <stdint.h>

typedef __nv_bfloat16 bf16;

#define S_LEN 2048
#define D_DIM 1024
#define F_DIM 3584
#define NCTA 128

__device__ __forceinline__ uint32_t smem_u32(const void* p) { return (uint32_t)__cvta_generic_to_shared(p); }
__device__ __forceinline__ void mbar_init(uint32_t bar, uint32_t count) {
  asm volatile("mbarrier.init.shared::cta.b64 [%0], %1;" ::"r"(bar), "r"(count) : "memory");
}
__device__ __forceinline__ void mbar_arrive(uint32_t bar) {
  asm volatile("mbarrier.arrive.shared::cta.b64 _, [%0];" ::"r"(bar) : "memory");
}
__device__ __forceinline__ void mbar_arrive_n(uint32_t bar, uint32_t n) {
  asm volatile("mbarrier.arrive.shared::cta.b64 _, [%0], %1;" ::"r"(bar), "r"(n) : "memory");
}
__device__ __forceinline__ void mbar_wait(uint32_t bar, uint32_t parity) {
  asm volatile(
      "{\n.reg .pred p;\n.reg .u32 c;\nmov.u32 c, 0;\n"
      "WAIT_LOOP:\n"
      "mbarrier.try_wait.parity.shared::cta.b64 p, [%0], %1;\n"
      "@p bra.uni WAIT_DONE;\n"
      "add.u32 c, c, 1;\n"
      "setp.lt.u32 p, c, 4194304;\n"
      "@p bra.uni WAIT_LOOP;\n"
      "trap;\n"
      "WAIT_DONE:\n}\n" ::"r"(bar), "r"(parity) : "memory");
}
__device__ __forceinline__ void prefetch_tmap(const CUtensorMap* tm) {
  asm volatile("prefetch.tensormap [%0];" ::"l"((uint64_t)tm) : "memory");
}
__device__ __forceinline__ void wgmma_fence() { asm volatile("wgmma.fence.sync.aligned;" ::: "memory"); }
__device__ __forceinline__ void wgmma_commit() { asm volatile("wgmma.commit_group.sync.aligned;" ::: "memory"); }
template <int N>
__device__ __forceinline__ void wgmma_wait() { asm volatile("wgmma.wait_group.sync.aligned %0;" ::"n"(N) : "memory"); }
__device__ __forceinline__ void bar_sync(int id, int nthreads) { asm volatile("bar.sync %0, %1;" ::"r"(id), "r"(nthreads) : "memory"); }
__device__ __forceinline__ void bar_arrive(int id, int nthreads) { asm volatile("bar.arrive %0, %1;" ::"r"(id), "r"(nthreads) : "memory"); }
__device__ __forceinline__ uint64_t make_desc(uint32_t addr, uint32_t lbo_bytes, uint32_t sbo_bytes) {
  uint64_t d = 0;
  d |= (uint64_t)((addr & 0x3FFFF) >> 4);
  d |= (uint64_t)((lbo_bytes & 0x3FFFF) >> 4) << 16;
  d |= (uint64_t)((sbo_bytes & 0x3FFFF) >> 4) << 32;
  d |= (uint64_t)1 << 62;
  return d;
}
template<int TA, int TB>
__device__ __forceinline__ void wgmma_n64(float (&d)[32], uint64_t da, uint64_t db, int scaleD) {
  asm volatile("{\n.reg .pred p;\nsetp.ne.b32 p, %34, 0;\n"
    "wgmma.mma_async.sync.aligned.m64n64k16.f32.bf16.bf16 {%0, %1, %2, %3, %4, %5, %6, %7, %8, %9, %10, %11, %12, %13, %14, %15, %16, %17, %18, %19, %20, %21, %22, %23, %24, %25, %26, %27, %28, %29, %30, %31}, %32, %33, p, 1, 1, %35, %36;\n}\n"
    : "+f"(d[0]), "+f"(d[1]), "+f"(d[2]), "+f"(d[3]), "+f"(d[4]), "+f"(d[5]), "+f"(d[6]), "+f"(d[7]), "+f"(d[8]), "+f"(d[9]), "+f"(d[10]), "+f"(d[11]), "+f"(d[12]), "+f"(d[13]), "+f"(d[14]), "+f"(d[15]), "+f"(d[16]), "+f"(d[17]), "+f"(d[18]), "+f"(d[19]), "+f"(d[20]), "+f"(d[21]), "+f"(d[22]), "+f"(d[23]), "+f"(d[24]), "+f"(d[25]), "+f"(d[26]), "+f"(d[27]), "+f"(d[28]), "+f"(d[29]), "+f"(d[30]), "+f"(d[31])
    : "l"(da), "l"(db), "r"(scaleD), "n"(TA), "n"(TB));
}

template<int TA, int TB>
__device__ __forceinline__ void wgmma_n96(float (&d)[48], uint64_t da, uint64_t db, int scaleD) {
  asm volatile("{\n.reg .pred p;\nsetp.ne.b32 p, %50, 0;\n"
    "wgmma.mma_async.sync.aligned.m64n96k16.f32.bf16.bf16 {%0, %1, %2, %3, %4, %5, %6, %7, %8, %9, %10, %11, %12, %13, %14, %15, %16, %17, %18, %19, %20, %21, %22, %23, %24, %25, %26, %27, %28, %29, %30, %31, %32, %33, %34, %35, %36, %37, %38, %39, %40, %41, %42, %43, %44, %45, %46, %47}, %48, %49, p, 1, 1, %51, %52;\n}\n"
    : "+f"(d[0]), "+f"(d[1]), "+f"(d[2]), "+f"(d[3]), "+f"(d[4]), "+f"(d[5]), "+f"(d[6]), "+f"(d[7]), "+f"(d[8]), "+f"(d[9]), "+f"(d[10]), "+f"(d[11]), "+f"(d[12]), "+f"(d[13]), "+f"(d[14]), "+f"(d[15]), "+f"(d[16]), "+f"(d[17]), "+f"(d[18]), "+f"(d[19]), "+f"(d[20]), "+f"(d[21]), "+f"(d[22]), "+f"(d[23]), "+f"(d[24]), "+f"(d[25]), "+f"(d[26]), "+f"(d[27]), "+f"(d[28]), "+f"(d[29]), "+f"(d[30]), "+f"(d[31]), "+f"(d[32]), "+f"(d[33]), "+f"(d[34]), "+f"(d[35]), "+f"(d[36]), "+f"(d[37]), "+f"(d[38]), "+f"(d[39]), "+f"(d[40]), "+f"(d[41]), "+f"(d[42]), "+f"(d[43]), "+f"(d[44]), "+f"(d[45]), "+f"(d[46]), "+f"(d[47])
    : "l"(da), "l"(db), "r"(scaleD), "n"(TA), "n"(TB));
}

template<int TA, int TB>
__device__ __forceinline__ void wgmma_n128(float (&d)[64], uint64_t da, uint64_t db, int scaleD) {
  asm volatile("{\n.reg .pred p;\nsetp.ne.b32 p, %66, 0;\n"
    "wgmma.mma_async.sync.aligned.m64n128k16.f32.bf16.bf16 {%0, %1, %2, %3, %4, %5, %6, %7, %8, %9, %10, %11, %12, %13, %14, %15, %16, %17, %18, %19, %20, %21, %22, %23, %24, %25, %26, %27, %28, %29, %30, %31, %32, %33, %34, %35, %36, %37, %38, %39, %40, %41, %42, %43, %44, %45, %46, %47, %48, %49, %50, %51, %52, %53, %54, %55, %56, %57, %58, %59, %60, %61, %62, %63}, %64, %65, p, 1, 1, %67, %68;\n}\n"
    : "+f"(d[0]), "+f"(d[1]), "+f"(d[2]), "+f"(d[3]), "+f"(d[4]), "+f"(d[5]), "+f"(d[6]), "+f"(d[7]), "+f"(d[8]), "+f"(d[9]), "+f"(d[10]), "+f"(d[11]), "+f"(d[12]), "+f"(d[13]), "+f"(d[14]), "+f"(d[15]), "+f"(d[16]), "+f"(d[17]), "+f"(d[18]), "+f"(d[19]), "+f"(d[20]), "+f"(d[21]), "+f"(d[22]), "+f"(d[23]), "+f"(d[24]), "+f"(d[25]), "+f"(d[26]), "+f"(d[27]), "+f"(d[28]), "+f"(d[29]), "+f"(d[30]), "+f"(d[31]), "+f"(d[32]), "+f"(d[33]), "+f"(d[34]), "+f"(d[35]), "+f"(d[36]), "+f"(d[37]), "+f"(d[38]), "+f"(d[39]), "+f"(d[40]), "+f"(d[41]), "+f"(d[42]), "+f"(d[43]), "+f"(d[44]), "+f"(d[45]), "+f"(d[46]), "+f"(d[47]), "+f"(d[48]), "+f"(d[49]), "+f"(d[50]), "+f"(d[51]), "+f"(d[52]), "+f"(d[53]), "+f"(d[54]), "+f"(d[55]), "+f"(d[56]), "+f"(d[57]), "+f"(d[58]), "+f"(d[59]), "+f"(d[60]), "+f"(d[61]), "+f"(d[62]), "+f"(d[63])
    : "l"(da), "l"(db), "r"(scaleD), "n"(TA), "n"(TB));
}

template<int TA, int TB>
__device__ __forceinline__ void wgmma_n192(float (&d)[96], uint64_t da, uint64_t db, int scaleD) {
  asm volatile("{\n.reg .pred p;\nsetp.ne.b32 p, %98, 0;\n"
    "wgmma.mma_async.sync.aligned.m64n192k16.f32.bf16.bf16 {%0, %1, %2, %3, %4, %5, %6, %7, %8, %9, %10, %11, %12, %13, %14, %15, %16, %17, %18, %19, %20, %21, %22, %23, %24, %25, %26, %27, %28, %29, %30, %31, %32, %33, %34, %35, %36, %37, %38, %39, %40, %41, %42, %43, %44, %45, %46, %47, %48, %49, %50, %51, %52, %53, %54, %55, %56, %57, %58, %59, %60, %61, %62, %63, %64, %65, %66, %67, %68, %69, %70, %71, %72, %73, %74, %75, %76, %77, %78, %79, %80, %81, %82, %83, %84, %85, %86, %87, %88, %89, %90, %91, %92, %93, %94, %95}, %96, %97, p, 1, 1, %99, %100;\n}\n"
    : "+f"(d[0]), "+f"(d[1]), "+f"(d[2]), "+f"(d[3]), "+f"(d[4]), "+f"(d[5]), "+f"(d[6]), "+f"(d[7]), "+f"(d[8]), "+f"(d[9]), "+f"(d[10]), "+f"(d[11]), "+f"(d[12]), "+f"(d[13]), "+f"(d[14]), "+f"(d[15]), "+f"(d[16]), "+f"(d[17]), "+f"(d[18]), "+f"(d[19]), "+f"(d[20]), "+f"(d[21]), "+f"(d[22]), "+f"(d[23]), "+f"(d[24]), "+f"(d[25]), "+f"(d[26]), "+f"(d[27]), "+f"(d[28]), "+f"(d[29]), "+f"(d[30]), "+f"(d[31]), "+f"(d[32]), "+f"(d[33]), "+f"(d[34]), "+f"(d[35]), "+f"(d[36]), "+f"(d[37]), "+f"(d[38]), "+f"(d[39]), "+f"(d[40]), "+f"(d[41]), "+f"(d[42]), "+f"(d[43]), "+f"(d[44]), "+f"(d[45]), "+f"(d[46]), "+f"(d[47]), "+f"(d[48]), "+f"(d[49]), "+f"(d[50]), "+f"(d[51]), "+f"(d[52]), "+f"(d[53]), "+f"(d[54]), "+f"(d[55]), "+f"(d[56]), "+f"(d[57]), "+f"(d[58]), "+f"(d[59]), "+f"(d[60]), "+f"(d[61]), "+f"(d[62]), "+f"(d[63]), "+f"(d[64]), "+f"(d[65]), "+f"(d[66]), "+f"(d[67]), "+f"(d[68]), "+f"(d[69]), "+f"(d[70]), "+f"(d[71]), "+f"(d[72]), "+f"(d[73]), "+f"(d[74]), "+f"(d[75]), "+f"(d[76]), "+f"(d[77]), "+f"(d[78]), "+f"(d[79]), "+f"(d[80]), "+f"(d[81]), "+f"(d[82]), "+f"(d[83]), "+f"(d[84]), "+f"(d[85]), "+f"(d[86]), "+f"(d[87]), "+f"(d[88]), "+f"(d[89]), "+f"(d[90]), "+f"(d[91]), "+f"(d[92]), "+f"(d[93]), "+f"(d[94]), "+f"(d[95])
    : "l"(da), "l"(db), "r"(scaleD), "n"(TA), "n"(TB));
}

template <int BN, int TA, int TB>
struct WG;
template <int TA, int TB> struct WG<96, TA, TB> { static __device__ __forceinline__ void mma(float (&d)[48], uint64_t a, uint64_t b) { wgmma_n96<TA, TB>(d, a, b, 1); } };
template <int TA, int TB> struct WG<128, TA, TB> { static __device__ __forceinline__ void mma(float (&d)[64], uint64_t a, uint64_t b) { wgmma_n128<TA, TB>(d, a, b, 1); } };
template <int TA, int TB> struct WG<192, TA, TB> { static __device__ __forceinline__ void mma(float (&d)[96], uint64_t a, uint64_t b) { wgmma_n192<TA, TB>(d, a, b, 1); } };

__device__ bf16 g_h[S_LEN * D_DIM];
__device__ bf16 g_o[S_LEN * D_DIM];
__device__ bf16 g_x2[S_LEN * D_DIM];
__device__ bf16 g_u[D_DIM * F_DIM];
__device__ uint4 g_statsA[S_LEN * 8];
__device__ uint4 g_statsB[S_LEN * 8];
__device__ uint4 g_halo[256 * 512];
__device__ uint4 g_cs[8 * 1536];
__device__ __align__(128) unsigned g_sync[32];
#define g_epoch g_sync[0]
#define g_exit g_sync[1]

#define PRE_NS 400
#define POLL_NS 100
#define HALO_NS 40
#define SKEL 0
#define SUD 1000
#define GRP 0
#define U1D 0
#define VAR 1
#define RHI 224
#define RLO 56
#define HOLD 0
#define PNORM 1
#define TV 1
#define FV 1
#define PREW 1
#define EPOLL 0
#define DP2 1
#define DP3A 1
#define DP3B 1
#define DP4 1
#define CK 0
#define PROWS 32
#define PACE 1

#define TRC(wg, r, i)
#define TRG(wg, r)
#define TRE(wg, id)
#define TRA(wg, id)

__device__ __forceinline__ int logical_cta(int mode) {
  uint32_t sm, nsm;
  asm volatile("mov.u32 %0, %smid;" : "=r"(sm));
  asm volatile("mov.u32 %0, %nsmid;" : "=r"(nsm));
  if (gridDim.x == 132 && nsm == 132) {
    const int t = sm >> 1;
    if (t == 60 || t == 61) return -1;
    const int g = t < 32 ? t & 7 : t < 60 ? 1 + (t - 32) % 7 : 0;
    const int i = (t < 32 ? t >> 3 : t < 60 ? 4 + (t - 32) / 7 : t - 58) * 2 + (sm & 1);
    if (mode == 0) return ((g >> 1) * 4 + (i >> 2)) * 8 + (g & 1) * 4 + (i & 3);
    if (mode == 1) return ((g >> 1) * 4 + (i & 3)) * 8 + (g & 1) * 4 + (i >> 2);
    if (mode == 2) return ((g & 3) * 4 + (i >> 2)) * 8 + (g >> 2) * 4 + (i & 3);
    if (mode == 3) return ((g >> 2) * 8 + (i >> 1)) * 8 + (g & 3) * 2 + (i & 1);
    return (g * 2 + (i >> 3)) * 8 + (i & 7);
  }
  const int b = blockIdx.x;
  if (b >= NCTA) return -1;
  const int g = b >> 3, i = b & 7, mq = g >> 2, jq = (mq & 1) ? 3 - (g & 3) : (g & 3);
  return ((mq * 4 + (i >> 1)) << 3) + jq * 2 + (i & 1);
}

__device__ __forceinline__ float tanh_fast(float x) {
  float y;
  asm("tanh.approx.f32 %0, %1;" : "=f"(y) : "f"(x));
  return y;
}
#define GELU_K01 (8.0f * 0.7978845608028654f * 0.044715f)
__device__ __forceinline__ float gelu_tanh(float hx, float k01) {
  const float k0 = 2.0f * 0.7978845608028654f;
  float t = hx * fmaf(hx * hx, k01, k0);
  return fmaf(hx, tanh_fast(t), hx);
}
__device__ __forceinline__ float ex2_fast(float x) {
  float y;
  asm("ex2.approx.ftz.f32 %0, %1;" : "=f"(y) : "f"(x));
  return y;
}
__device__ __forceinline__ uint32_t pack2(float a, float b) {
  __nv_bfloat162 v = __floats2bfloat162_rn(a, b);
  return *reinterpret_cast<uint32_t*>(&v);
}
__device__ __forceinline__ float bf_lo(uint32_t v) { return __uint_as_float(v << 16); }
__device__ __forceinline__ float bf_hi(uint32_t v) { return __uint_as_float(v & 0xffff0000u); }
__device__ __forceinline__ void unpack8(const uint4& t, float (&f)[8]) {
  f[0] = bf_lo(t.x); f[1] = bf_hi(t.x); f[2] = bf_lo(t.y); f[3] = bf_hi(t.y);
  f[4] = bf_lo(t.z); f[5] = bf_hi(t.z); f[6] = bf_lo(t.w); f[7] = bf_hi(t.w);
}
__device__ __forceinline__ uint4 pack8(const float (&f)[8]) {
  return make_uint4(pack2(f[0], f[1]), pack2(f[2], f[3]), pack2(f[4], f[5]), pack2(f[6], f[7]));
}
__device__ __forceinline__ int opaque_tid() { int v; asm volatile("mov.u32 %0, %tid.x;" : "=r"(v)); return v; }
__device__ __forceinline__ uint4 lds128(uint32_t a) {
  uint4 v;
  asm volatile("ld.shared.v4.u32 {%0,%1,%2,%3}, [%4];" : "=r"(v.x), "=r"(v.y), "=r"(v.z), "=r"(v.w) : "r"(a) : "memory");
  return v;
}
__device__ __forceinline__ float2 lds64f(uint32_t a) {
  float2 v;
  asm volatile("ld.shared.v2.f32 {%0,%1}, [%2];" : "=f"(v.x), "=f"(v.y) : "r"(a) : "memory");
  return v;
}
__device__ __forceinline__ uint32_t lds32(uint32_t a) {
  uint32_t v;
  asm volatile("ld.shared.u32 %0, [%1];" : "=r"(v) : "r"(a) : "memory");
  return v;
}
__device__ __forceinline__ void sts128(uint32_t a, const uint4& v) {
  asm volatile("st.shared.v4.u32 [%0], {%1,%2,%3,%4};" ::"r"(a), "r"(v.x), "r"(v.y), "r"(v.z), "r"(v.w) : "memory");
}
__device__ __forceinline__ void sts32(uint32_t a, uint32_t x) {
  asm volatile("st.shared.u32 [%0], %1;" ::"r"(a), "r"(x) : "memory");
}
__device__ __forceinline__ void sts64(uint32_t a, uint32_t x, uint32_t y) {
  asm volatile("st.shared.v2.u32 [%0], {%1,%2};" ::"r"(a), "r"(x), "r"(y) : "memory");
}
__device__ __forceinline__ void sts64f(uint32_t a, float x, float y) {
  asm volatile("st.shared.v2.f32 [%0], {%1,%2};" ::"r"(a), "f"(x), "f"(y) : "memory");
}
__device__ __forceinline__ void stmatrix4(uint32_t a, uint32_t r0, uint32_t r1, uint32_t r2, uint32_t r3) {
  asm volatile("stmatrix.sync.aligned.m8n8.x4.shared.b16 [%0], {%1,%2,%3,%4};" ::"r"(a), "r"(r0), "r"(r1), "r"(r2), "r"(r3) : "memory");
}
__device__ __forceinline__ void ldmatrix4(uint32_t (&r)[4], uint32_t a) {
  asm volatile("ldmatrix.sync.aligned.m8n8.x4.shared.b16 {%0,%1,%2,%3}, [%4];" : "=r"(r[0]), "=r"(r[1]), "=r"(r[2]), "=r"(r[3]) : "r"(a) : "memory");
}
__device__ __forceinline__ uint32_t movmatrix_t(uint32_t a) {
  uint32_t d;
  asm volatile("movmatrix.sync.aligned.m8n8.trans.b16 %0, %1;" : "=r"(d) : "r"(a));
  return d;
}
__device__ __forceinline__ void mma16816(float (&c)[4], uint32_t a0, uint32_t a1, uint32_t a2, uint32_t a3, uint32_t b0, uint32_t b1) {
  asm volatile("mma.sync.aligned.m16n8k16.row.col.f32.bf16.bf16.f32 {%0,%1,%2,%3}, {%4,%5,%6,%7}, {%8,%9}, {%0,%1,%2,%3};"
               : "+f"(c[0]), "+f"(c[1]), "+f"(c[2]), "+f"(c[3]) : "r"(a0), "r"(a1), "r"(a2), "r"(a3), "r"(b0), "r"(b1));
}
__device__ __forceinline__ void mma1688(float (&c)[4], uint32_t a0, uint32_t a1, uint32_t b0) {
  asm volatile("mma.sync.aligned.m16n8k8.row.col.f32.bf16.bf16.f32 {%0,%1,%2,%3}, {%4,%5}, {%6}, {%0,%1,%2,%3};"
               : "+f"(c[0]), "+f"(c[1]), "+f"(c[2]), "+f"(c[3]) : "r"(a0), "r"(a1), "r"(b0));
}
__device__ __forceinline__ uint4 ld_volatile4(const uint4* p) {
  uint4 v;
  asm volatile("ld.relaxed.gpu.global.v4.u32 {%0,%1,%2,%3}, [%4];" : "=r"(v.x), "=r"(v.y), "=r"(v.z), "=r"(v.w) : "l"(p) : "memory");
  return v;
}
__device__ __forceinline__ void red_release(unsigned* p) {
  asm volatile("fence.proxy.async;\nred.relaxed.gpu.global.add.u32 [%0], 1;" ::"l"(p) : "memory");
}
__device__ __forceinline__ void tma_store(const CUtensorMap* tm, uint32_t src, int c0, int c1, int c2, int c3) {
  asm volatile("cp.async.bulk.tensor.4d.global.shared::cta.bulk_group [%0, {%2, %3, %4, %5}], [%1];" ::"l"((uint64_t)tm), "r"(src),
               "r"(c0), "r"(c1), "r"(c2), "r"(c3) : "memory");
}
__device__ __forceinline__ void bulk_commit() { asm volatile("cp.async.bulk.commit_group;" ::: "memory"); }
template <int N>
__device__ __forceinline__ void bulk_wait() { asm volatile("cp.async.bulk.wait_group %0;" ::"n"(N) : "memory"); }
template <int N>
__device__ __forceinline__ void bulk_wait_read() { asm volatile("cp.async.bulk.wait_group.read %0;" ::"n"(N) : "memory"); }
__device__ __forceinline__ void fence_proxy_async_smem() { asm volatile("fence.proxy.async.shared::cta;" ::: "memory"); }
__device__ __forceinline__ void spin_until(const unsigned* p, unsigned target) {
  asm volatile(
      "{\n.reg .pred p;\n.reg .u32 v0, v1, c;\nmov.u32 c, 0;\n"
      "ld.relaxed.gpu.global.u32 v0, [%0];\n"
      "nanosleep.u32 150;\n"
      "SPIN_LOOP:\n"
      "ld.relaxed.gpu.global.u32 v1, [%0];\n"
      "sub.u32 v0, v0, %1;\n"
      "setp.ge.s32 p, v0, 0;\n"
      "@p bra.uni SPIN_DONE;\n"
      "ld.relaxed.gpu.global.u32 v0, [%0];\n"
      "sub.u32 v1, v1, %1;\n"
      "setp.ge.s32 p, v1, 0;\n"
      "@p bra.uni SPIN_DONE;\n"
      "add.u32 c, c, 1;\n"
      "setp.lt.u32 p, c, 4194304;\n"
      "@p bra.uni SPIN_LOOP;\n"
      "trap;\n"
      "SPIN_DONE:\n"
      "fence.acquire.gpu;\n}\n" ::"l"(p), "r"(target) : "memory");
}
__device__ __forceinline__ void e_expect_tx(uint32_t bar, uint32_t bytes) {
  asm volatile("{\n.reg .pred p;\nelect.sync _|p, 0xffffffff;\n@p mbarrier.arrive.expect_tx.shared::cta.b64 _, [%0], %1;\n}\n" ::"r"(bar), "r"(bytes) : "memory");
}
__device__ __forceinline__ void e_tma_load(uint32_t dst, const CUtensorMap* tm, uint32_t bar, int c0, int c1, int c2, int c3) {
  asm volatile(
      "{\n.reg .pred p;\nelect.sync _|p, 0xffffffff;\n"
      "@p cp.async.bulk.tensor.4d.shared::cluster.global.mbarrier::complete_tx::bytes [%0], [%1, {%3, %4, %5, %6}], [%2];\n}\n" ::"r"(dst),
      "l"((uint64_t)tm), "r"(bar), "r"(c0), "r"(c1), "r"(c2), "r"(c3) : "memory");
}

__device__ __forceinline__ void e_tma_prefetch(const CUtensorMap* tm, int c0, int c1, int c2) {
  asm volatile(
      "{\n.reg .pred p;\nelect.sync _|p, 0xffffffff;\n"
      "@p cp.async.bulk.prefetch.tensor.4d.L2.global [%0, {%1, %2, %3, %4}];\n}\n" ::"l"((uint64_t)tm), "r"(c0), "r"(c1), "r"(c2), "r"(0) : "memory");
}

#define RING_U 24
#define OFF_STG (RING_U * 8192)
#define OFF_BAR (OFF_STG + 32768)
#define OFF_FULL (OFF_BAR)
#define OFF_EMPTY (OFF_BAR + 192)
#define OFF_STR (OFF_BAR + 256)
#define OFF_OST (OFF_BAR + 272)
#define OFF_TR (OFF_BAR + 288)
#define OFF_TU0 (OFF_BAR + 304)
#define OFF_TU1 (OFF_BAR + 320)
#define OFF_SFR (OFF_BAR + 336)
#define OFF_K01 (OFF_BAR + 352)
#define OFF_HOLD (OFF_BAR + 368)
#define OFF_DEP (OFF_B2 + 256)
#define OFF_CS (OFF_BAR + 384)
#define OFF_ST (OFF_CS + 768)
#define OFF_B1 (OFF_ST + 1024)
#define OFF_B2 (OFF_B1 + 448)
#define SMEM_TOTAL (OFF_B2 + 256 + 80)

enum { K_G1 = 0, K_RES = 2, K_G2 = 4, K_G3 = 6, K_G3S = 8, K_G4 = 9, K_G4S = 11 };
enum { E_O = 1, E_H = 3, E_UA = 5, E_UB = 6, E_U1 = 7, E_X = 8 };
#define MAXSEG 80
#define MAXRUN 48

struct Params {
  CUtensorMap xq[2], xr[2], x2m, wqkv, o_k, wo, h_m, w1a, w1b, w1h, w2s, w2d, u_k, o_s, out_s, u_s, u_h;
  uint2 seg[MAXSEG];
  uint32_t run[2][MAXRUN];
  int nseg;
  uint32_t pre, poll, u1d, sud, map;
};

#define LCTA __shfl_sync(0xffffffffu, (int)lds32(sbase + OFF_K01 + 8), 0)
#define opaque_cta() LCTA

template <int WHICH>
__device__ __forceinline__ void producer(const Params& P, uint32_t sbase) {
  const int cta = LCTA, m = cta >> 3, j = cta & 7;
  uint32_t tail8 = 0;
  const int nseg = P.nseg;
#pragma unroll 1
  for (int si = 0; si < nseg; si++) {
    const uint32_t sg = P.seg[si].x;
    if (WHICH == 1 && ((sg >> 28) & 1)) continue;
    const int kind = sg & 15, n = (sg >> 10) & 63, ks = (((sg >> 16) & 1) + 1) * 64, dep = (sg >> 17) & 31, l = (sg >> 27) & 1;
    const int kk = ((sg >> 4) & 63) * 64;
    const int w = (kind < K_G3S ? kind : kind - 1) & 1;
    const int set = (kind == K_G3S || kind == K_G4S) ? 2 : w;
    const CUtensorMap* mp;
    int c0 = kk, c1 = kk, c3 = 0, d0 = 0, d1 = ks, size, soff, nx = 0;
    uint32_t bytes;
    if (kind < K_RES) {
      size = 6;
      if (WHICH == 0) { mp = &P.wqkv; c0 = m * 64; soff = 16384; bytes = 24576; }
      else { mp = &P.xq[l]; c1 = 0; c3 = w * 16 + j * 2; d0 = ks; d1 = 0; soff = 0; bytes = 16384; }
    } else if (kind < K_G2) {
      size = 3;
      mp = &P.xr[l]; c0 = j * 128 + WHICH * 64; c1 = (w * 16 + m) * 64; soff = WHICH * 8192; bytes = 8192;
    } else if (kind < K_G3) {
      size = 3;
      if (WHICH == 0) { mp = &P.wo; c0 = j * 128; soff = 0; bytes = 16384; }
      else { mp = &P.o_k; c1 = (w * 16 + m) * 64; d0 = ks; d1 = 0; soff = 16384; bytes = 8192; }
    } else if (kind < K_G4) {
      size = kind == K_G3S ? 6 : 4;
      if (WHICH == 0) {
        soff = 16384;
        if (kind == K_G3 + 1) { mp = &P.w1b; c0 = 2048 + m * 96 + (m & 1) * 32; nx = 1; bytes = 16384; }
        else { mp = &P.w1a; c0 = m * 128; nx = kind == K_G3S ? 2 : 0; bytes = kind == K_G3S ? 32768 : 16384; }
      } else { mp = &P.h_m; c0 = j * 128; soff = 0; bytes = 16384; }
    } else {
      size = kind == K_G4S ? 4 : 3;
      if (WHICH == 0) {
        soff = 16384;
        if (kind == K_G4S) { mp = &P.w2d; c0 = m * 64; bytes = 16384; }
        else { mp = &P.w2s; c0 = (w * 16 + m) * 64; bytes = 8192; }
      } else { mp = &P.u_k; c1 = j * 128; d0 = ks; d1 = 0; soff = 0; bytes = 16384; }
    }
    if (WHICH == 0 && ((sg >> 28) & 1)) {
      const bool byj = kind >= K_G2 && kind < K_G3;
#pragma unroll 1
      for (int i = byj ? m : j; i < n; i += byj ? 16 : 8) {
        const int kp = kk + i * ks;
        e_tma_prefetch(mp, c0, kp, 0);
        if (nx == 2) e_tma_prefetch(&P.w1b, 2048 + m * 96 + (m & 1) * 32, kp, 0);
        if (nx && !(m & 1)) e_tma_prefetch(&P.w1b, 2048 + m * 96 + 64, kp, 0);
      }
      continue;
    }
    uint32_t wc = P.seg[si].y;
    const uint32_t fb0 = sbase + OFF_FULL + set * 64, dst0 = sbase + soff, step = size * 8192;
    uint32_t fb = fb0 + (wc >> 29) * 8, dst = dst0 + ((sg >> 22) & 31) * 8192;
    wc = (wc & 0x0fffffffu) | 0x50000000u;
    if (WHICH == 1 && !SKEL && dep) {
      mbar_wait(sbase + OFF_DEP + (dep & 15) * 8, dep >> 4);
      asm volatile("fence.proxy.async.global;" ::: "memory");
    }
#pragma unroll 1
    for (int i = n; i > 0; i--) {
#pragma unroll 1
      for (uint32_t q = wc & 3; q; q--) {
        mbar_wait(sbase + OFF_EMPTY + (tail8 & 0x38), (tail8 >> 6) & 1);
        tail8 += 8;
      }
      e_tma_load(dst, mp, fb, c0, c1, 0, c3);
      if (WHICH == 0 && nx) {
        if (nx == 2) e_tma_load(dst + 16384, &P.w1b, fb, 2048 + m * 96 + (m & 1) * 32, c1, 0, 0);
        e_tma_load(dst + nx * 16384 - 8192, &P.w1h, fb, 0, c1, 64 + m * 3 + 2 - (m & 1) * 2, 0);
      }
      e_expect_tx(fb, bytes);
      wc = (wc >> 2) | 0x40000000u;
      c0 += d0; c1 += d1;
      fb = fb == fb0 + 56 ? fb0 : fb + 8;
      dst += step;
      if (dst == dst0 + RING_U * 8192) dst = dst0;
    }
  }
}

struct Cons {
  uint32_t nsolo, nshr;
  int ri;
  uint32_t prev;
};
template <int MW, int BN, int TA, int TB, int SZ0, int SZ1, int AOFF, int BOFF, int ASH, int BSH, int DP>
__device__ __forceinline__ void gemm_runs(const Params& P, uint32_t sbase, Cons& c, float (&acc)[MW][BN / 2], int wg) {
  uint32_t prev = 0, prev2 = 0;
  uint32_t r;
#pragma unroll
  for (int b = 0; b < MW; b++)
#pragma unroll
    for (int i = 0; i < BN / 2; i++) asm volatile("" : "+f"(acc[b][i])::"memory");
  const bool lead = (threadIdx.x & 127) == 0;
  if (DP == 2) { wgmma_fence(); wgmma_commit(); wgmma_commit(); }
#pragma unroll 1
  do {
    r = P.run[wg][c.ri];
    const int sh = (r >> 14) & 1, pre = (r >> 15) & 15, post = (r >> 19) & 15;
    uint32_t so = ((r >> 6) & 31) * 512, e8 = (r >> 8) & 0x38;
    const uint32_t size = (sh ? SZ1 : SZ0) * 512;
    uint32_t cnt = sh ? c.nshr : c.nsolo;
    const uint32_t fb0 = sbase + OFF_FULL + (sh ? 2 : wg) * 64, eb0 = sbase + OFF_EMPTY + 2 - sh;
    const uint64_t da0 = make_desc(sbase + AOFF + (sh ? ASH * wg : 0), TA ? 8192 : 16, 1024);
    const uint64_t db0 = make_desc(sbase + BOFF + (sh ? BSH * wg : 0), TB ? 8192 : 16, 1024);
    TRC(wg, c.ri, 0);
    if (pre) bar_sync(pre, 256);
    int i = r & 63;
#pragma unroll 1
    do {
      mbar_wait(fb0 + (cnt & 7) * 8, (cnt >> 3) & 1);
      wgmma_fence();
#pragma unroll
      for (int k = 0; k < 4; k++) {
#pragma unroll
        for (int b = 0; b < MW; b++)
          WG<BN, TA, TB>::mma(acc[b], da0 + so + b * 512 + (TA ? k * 128 : k * 2), db0 + so + (TB ? k * 128 : k * 2));
        if (k == (DP == 3 ? CK : 3)) wgmma_commit();
      }
      if (post && i == 1) bar_arrive(post, 256);
      cnt++;
      so += size;
      if (so == RING_U * 512) so = 0;
      wgmma_wait<DP == 2 ? 2 : 1>();
      const uint32_t rel = DP >= 2 ? prev2 : prev;
      if (rel && lead) mbar_arrive_n(rel & ~7u, rel & 7);
      prev2 = prev;
      prev = eb0 + e8;
      e8 = (e8 + 8) & 0x38;
    } while (--i);
    if (sh) c.nshr = cnt; else c.nsolo = cnt;
    if (r & (1u << 23)) {
      if (DP == 3) wgmma_commit();
      wgmma_wait<0>();
      if (DP >= 2 && prev2 && lead) mbar_arrive_n(prev2 & ~7u, prev2 & 7);
      if (lead) mbar_arrive_n(prev & ~7u, prev & 7);
      prev = prev2 = 0;
    }
    TRC(wg, c.ri, 3);
    c.ri++;
  } while (!(r & (1u << 24)));
  if (BN == 192) { c.prev = prev & ~7u; return; }
  if (DP == 3) wgmma_commit();
  wgmma_wait<0>();
#pragma unroll
  for (int b = 0; b < MW; b++)
#pragma unroll
    for (int i = 0; i < BN / 2; i++) asm volatile("" : "+f"(acc[b][i])::"memory");
}

__device__ __forceinline__ void stage_tile128(const uint32_t (&pk)[32], uint32_t wbase, int lane) {
  const int r7 = lane & 7;
  const uint32_t sa = wbase + (((lane >> 3) & 1) * 8 + r7) * 128;
#pragma unroll
  for (int j = 0; j < 8; j++)
    stmatrix4(sa + (j >> 2) * 8192 + ((((j * 2 + (lane >> 4)) & 7) ^ r7) << 4), pk[j * 4 + 0], pk[j * 4 + 1], pk[j * 4 + 2], pk[j * 4 + 3]);
}
__device__ __forceinline__ void tile_stats(const float (&acc)[64], uint4* dst, unsigned tag, int t) {
  float s0 = 0.f, s1 = 0.f, s2 = 0.f, s3 = 0.f, q0 = 0.f, q1 = 0.f, q2 = 0.f, q3 = 0.f;
#pragma unroll
  for (int j = 0; j < 16; j++) {
    s0 += acc[j * 4 + 0]; s2 += acc[j * 4 + 1]; s1 += acc[j * 4 + 2]; s3 += acc[j * 4 + 3];
    q0 = fmaf(acc[j * 4 + 0], acc[j * 4 + 0], q0); q2 = fmaf(acc[j * 4 + 1], acc[j * 4 + 1], q2);
    q1 = fmaf(acc[j * 4 + 2], acc[j * 4 + 2], q1); q3 = fmaf(acc[j * 4 + 3], acc[j * 4 + 3], q3);
  }
  s0 += s2; s1 += s3; q0 += q2; q1 += q3;
  float s = (t & 1) ? s1 : s0, q = (t & 1) ? q1 : q0;
  s += __shfl_xor_sync(0xffffffffu, (t & 1) ? s0 : s1, 1); q += __shfl_xor_sync(0xffffffffu, (t & 1) ? q0 : q1, 1);
  s += __shfl_xor_sync(0xffffffffu, s, 2); q += __shfl_xor_sync(0xffffffffu, q, 2);
  if (t < 2) __stcg(dst + t * 8, make_uint4(__float_as_uint(s), tag, __float_as_uint(q), tag));
}
__device__ __forceinline__ void store_rows(const CUtensorMap* mp, uint32_t src, int col, int row, uint32_t bar, int lane) {
  fence_proxy_async_smem();
  __syncwarp();
  if (lane == 0) {
    tma_store(mp, src, col, row, 0, 0);
    tma_store(mp, src + 8192, col + 64, row, 0, 0);
    bulk_commit();
    bulk_wait<0>();
    if (bar) mbar_arrive(bar);
  }
  __syncwarp();
}

__device__ __forceinline__ void attention(const Params& P, float (&acc)[2][96], uint32_t sbase, Cons& c, int wg, int l, unsigned tag) {
  const uint32_t r = P.run[wg][c.ri];
  const uint32_t slot0 = sbase + OFF_STG + wg * 16384;
  TRC(wg, c.ri, 0);
        if (PREW) {
          const int cta = opaque_cta(), tid = opaque_tid();
          if (tid & 32) {
            uint4* hp = &g_halo[((wg * 8 + (cta & 7)) * 16 + (cta >> 3)) * 512 + ((tid >> 6) & 1) * 256 + (tid & 31)];
#pragma unroll
            for (int i = 0; i < 8; i++) __stcg(hp + i * 32, make_uint4(0, 0, 0, 0));
          }
        }
  const uint64_t da0 = make_desc(sbase, 16, 1024), db0 = make_desc(sbase + 16384, 8192, 1024);
  const uint32_t so0 = ((r >> 6) & 31) * 512, so1 = so0 == (RING_U - 6) * 512 ? 0 : so0 + 6 * 512, so2 = so1 == (RING_U - 6) * 512 ? 0 : so1 + 6 * 512;
  {
    uint32_t so = so0;
#pragma unroll 1
    for (int i = 0; i < 3; i++) {
      mbar_wait(sbase + OFF_FULL + wg * 64 + (c.nsolo & 7) * 8, (c.nsolo >> 3) & 1);
      if (i == 0) TRC(wg, c.ri, 2);
      c.nsolo++;
      wgmma_fence();
#pragma unroll
      for (int k = 0; k < 4; k++) WG<192, 0, 1>::mma(acc[1], da0 + so + 512 + k * 2, db0 + so + k * 128);
      wgmma_commit();
      wgmma_wait<1>();
      if (i == 0 && (threadIdx.x & 127) == 0) mbar_arrive_n(c.prev, 2);
      so = so == (RING_U - 6) * 512 ? 0 : so + 6 * 512;
    }
  }
#define TAIL(so)                                                                                                           \
  _Pragma("unroll") for (int k = 0; k < 4; k++) WG<192, 0, 1>::mma(acc[0], da0 + (so) + k * 2, db0 + (so) + k * 128);      \
  wgmma_commit()
#define EB(i) (sbase + OFF_EMPTY + (((r >> 11) + (i)) & 7) * 8)
#define PIN(b, i0, i1) _Pragma("unroll") for (int i = i0; i < i1; i++) asm volatile("" : "+f"(acc[b][i])::"memory")
#define PK(b, jj, h) pack2(acc[b][(jj) * 4 + (h) * 2], acc[b][(jj) * 4 + (h) * 2 + 1])
  mbar_wait(sbase + OFF_STR + wg * 8, l);
  {
    const uint64_t de = (uint64_t)((slot0 & 0x3FFFF) >> 4) | ((uint64_t)8 << 32);
    wgmma_fence();
    wgmma_n192<0, 0>(acc[1], de + 64, de + 128, 1);
    wgmma_commit();
    wgmma_n192<0, 0>(acc[0], de, de + 128, 1);
  }
  TAIL(so0);
  TAIL(so1);
  const int cta = opaque_cta(), tid = opaque_tid(), lane = tid & 31, g = lane >> 2, t = lane & 3;
  const int wq = __shfl_sync(0xffffffffu, (tid >> 5) & 3, 0), hf = wq & 1;
  const int T = wg * 8 + (cta & 7), tn = cta >> 3;
  uint4* const hp = &g_halo[(T * 16 + tn) * 512 + (wq >> 1) * 256 + lane];
  uint32_t Q[2][8][2], K[2][8][2], V[2][8][2];
#define PACKKV(b)                                                                                       \
  _Pragma("unroll") for (int jj = 7; jj >= 0; jj--) {                                                   \
    V[b][jj][1] = movmatrix_t(PK(b, jj + 16, 1)); V[b][jj][0] = PK(b, jj + 16, 0);                      \
  }                                                                                                     \
  _Pragma("unroll") for (int jj = 7; jj >= 0; jj--) { K[b][jj][1] = PK(b, jj + 8, 1); K[b][jj][0] = PK(b, jj + 8, 0); }
#define PACKQ(b)                                                                                        \
  _Pragma("unroll") for (int jj = 7; jj >= 0; jj--) {                                                   \
    V[b][jj][0] = movmatrix_t(V[b][jj][0]); Q[b][jj][1] = PK(b, jj, 1); Q[b][jj][0] = PK(b, jj, 0);     \
  }
#define HALO_OUT(b, a)                                                                                  \
  sts128(a, make_uint4(K[b][0][1], K[b][1][1], K[b][2][1], K[b][3][1]));                                \
  sts128(a + 512, make_uint4(K[b][4][1], K[b][5][1], K[b][6][1], K[b][7][1]));                          \
  sts128(a + 1024, make_uint4(V[b][0][1], V[b][1][1], V[b][2][1], V[b][3][1]));                         \
  sts128(a + 1536, make_uint4(V[b][4][1], V[b][5][1], V[b][6][1], V[b][7][1]))
  wgmma_wait<TV ? 2 : 3>();
  PIN(1, 0, 96);
  TRE(wg, l * 32 + 1);
  PACKKV(1);
  if (!hf) { HALO_OUT(1, slot0 + (5 + wq) * 2048 + lane * 16); }
  else if (T < 15) {
#pragma unroll
    for (int i = 0; i < 4; i++) {
      __stcg(hp + i * 32, make_uint4(K[1][i * 2][1], tag, K[1][i * 2 + 1][1], tag));
      __stcg(hp + (i + 4) * 32, make_uint4(V[1][i * 2][1], tag, V[1][i * 2 + 1][1], tag));
    }
  }
  TRE(wg, l * 32 + 2);
  wgmma_fence();
  TAIL(so2);
  wgmma_wait<2>();
  if ((tid & 127) == 0) mbar_arrive_n(EB(0), 2);
  PACKQ(1);
  wgmma_wait<1>();
  if ((r >> 19) & 15) bar_arrive((r >> 19) & 15, 256);
  if ((tid & 127) == 0) mbar_arrive_n(EB(1), 2);
  const bool o0 = 2 * t > g, o1 = 2 * t + 1 > g;
  float rk[2][4], rq[2][4];
#pragma unroll
  for (int b = 0; b < 2; b++) {
    const uint32_t a = sbase + OFF_ST + ((wq >> 1) * 72 + 8 + b * 32 + hf * 16) * 4;
    const float kscale = 0.17677669529663687f * 1.4426950408889634f;
    const float q0 = __uint_as_float(lds32(a + g * 4)) * kscale, q1 = __uint_as_float(lds32(a + g * 4 + 32)) * kscale;
    const uint32_t a0 = a + t * 8 - (o0 ? 32 : 0), a1 = a + t * 8 + 4 - (o1 ? 32 : 0);
    rk[b][0] = __uint_as_float(lds32(a0)); rk[b][1] = __uint_as_float(lds32(a1));
    rk[b][2] = __uint_as_float(lds32(a0 + 32)); rk[b][3] = __uint_as_float(lds32(a1 + 32));
    rq[b][0] = rk[b][0] * q0; rq[b][1] = rk[b][1] * q0; rq[b][2] = rk[b][2] * q1; rq[b][3] = rk[b][3] * q1;
  }
  const bool remote = !hf && T > 0 && !SKEL;
  wgmma_wait<0>();
  PIN(0, 0, 96);
  if ((tid & 127) == 0) mbar_arrive_n(EB(2), 2);
  uint4 hv[8];
#pragma unroll
  for (int i = 0; i < 8; i++)
    asm volatile("{\n.reg .pred p;\nsetp.ne.u32 p, %5, 0;\nmov.u32 %0, 0;\nmov.u32 %1, 0;\nmov.u32 %2, 0;\nmov.u32 %3, 0;\n"
                 "@p ld.relaxed.gpu.global.v4.u32 {%0,%1,%2,%3}, [%4];\n}\n"
                 : "=&r"(hv[i].x), "=&r"(hv[i].y), "=&r"(hv[i].z), "=&r"(hv[i].w) : "l"(hp - 16 * 512 + i * 32), "r"((int)remote) : "memory");
  TRC(wg, c.ri, 3);
  c.ri++;
  PACKKV(0);
  HALO_OUT(0, slot0 + (hf ? 3 + wq : 1 + wq) * 2048 + lane * 16);
  PACKQ(0);
  TRE(wg, l * 32 + 29);
  bar_sync(7 + wg, 128);
  uint32_t HK[2][8], HV[2][8];
#pragma unroll
  for (int b = 1; b >= 0; b--) {
    if (b == 1 || hf) {
      const uint32_t a = slot0 + (b * 4 + wq) * 2048 + lane * 16;
      const uint4 k0 = lds128(a), k1 = lds128(a + 512), v0 = lds128(a + 1024), v1 = lds128(a + 1536);
      HK[b][0] = k0.x; HK[b][1] = k0.y; HK[b][2] = k0.z; HK[b][3] = k0.w; HK[b][4] = k1.x; HK[b][5] = k1.y; HK[b][6] = k1.z; HK[b][7] = k1.w;
      HV[b][0] = v0.x; HV[b][1] = v0.y; HV[b][2] = v0.z; HV[b][3] = v0.w; HV[b][4] = v1.x; HV[b][5] = v1.y; HV[b][6] = v1.z; HV[b][7] = v1.w;
    } else {
      if (remote) {
#pragma unroll 1
        for (int it = 0; it < (1 << 20); it++) {
          bool ok = true;
#pragma unroll
          for (int i = 0; i < 8; i++) ok = ok && hv[i].y == tag && hv[i].w == tag;
          if (__all_sync(0xffffffffu, ok)) break;
          __nanosleep(HALO_NS);
#pragma unroll
          for (int i = 0; i < 8; i++) hv[i] = ld_volatile4(hp - 16 * 512 + i * 32);
        }
      }
#pragma unroll
      for (int i = 0; i < 4; i++) { HK[0][i * 2] = hv[i].x; HK[0][i * 2 + 1] = hv[i].z; HV[0][i * 2] = hv[i + 4].x; HV[0][i * 2 + 1] = hv[i + 4].z; }
    }
  }
  TRE(wg, l * 32 + 3);
  float S[2][2][3][4];
#pragma unroll
  for (int b = 1; b >= 0; b--)
#pragma unroll
    for (int u = 0; u < 2; u++)
#pragma unroll
      for (int kt = 0; kt < 3; kt++) S[b][u][kt][0] = S[b][u][kt][1] = S[b][u][kt][2] = S[b][u][kt][3] = 0.f;
#pragma unroll
  for (int ks = 0; ks < 2; ks++)
#pragma unroll
    for (int b = 1; b >= 0; b--)
#pragma unroll
      for (int u = 0; u < 2; u++) {
        const int j0 = u * 4 + ks * 2;
        mma16816(S[b][u][1], Q[b][j0][0], Q[b][j0][1], Q[b][j0 + 1][0], Q[b][j0 + 1][1], K[b][j0][0], K[b][j0 + 1][0]);
        mma16816(S[b][u][2], Q[b][j0][0], Q[b][j0][1], Q[b][j0 + 1][0], Q[b][j0 + 1][1], K[b][j0][1], K[b][j0 + 1][1]);
        mma16816(S[b][u][0], Q[b][j0][0], Q[b][j0][1], Q[b][j0 + 1][0], Q[b][j0 + 1][1], HK[b][j0], HK[b][j0 + 1]);
      }
  TRE(wg, l * 32 + 4);
  const uint32_t mold = (o0 ? 0xffffu : 0u) | (o1 ? 0xffff0000u : 0u);
  const float NEG = -3.0e38f;
  const bool first = T == 0 && !hf;
  uint32_t pl[2][2], ph[2][2];
#pragma unroll
  for (int b = 1; b >= 0; b--)
#pragma unroll
    for (int u = 0; u < 2; u++) {
      float a0 = (o0 ? S[b][u][0][0] : S[b][u][1][0]) * rq[b][0], a1 = (o1 ? S[b][u][0][1] : S[b][u][1][1]) * rq[b][1];
      float b0 = (o0 ? S[b][u][1][2] : S[b][u][2][2]) * rq[b][2], b1 = (o1 ? S[b][u][1][3] : S[b][u][2][3]) * rq[b][3];
      if (b == 0) { a0 = (first && o0) ? NEG : a0; a1 = (first && o1) ? NEG : a1; }
      float m0 = fmaxf(a0, a1), m1 = fmaxf(b0, b1);
      m0 = fmaxf(m0, __shfl_xor_sync(0xffffffffu, m0, 1)); m1 = fmaxf(m1, __shfl_xor_sync(0xffffffffu, m1, 1));
      m0 = fmaxf(m0, __shfl_xor_sync(0xffffffffu, m0, 2)); m1 = fmaxf(m1, __shfl_xor_sync(0xffffffffu, m1, 2));
      a0 = ex2_fast(a0 - m0); a1 = ex2_fast(a1 - m0); b0 = ex2_fast(b0 - m1); b1 = ex2_fast(b1 - m1);
      float s0 = a0 + a1, s1 = b0 + b1;
      s0 += __shfl_xor_sync(0xffffffffu, s0, 1); s1 += __shfl_xor_sync(0xffffffffu, s1, 1);
      s0 += __shfl_xor_sync(0xffffffffu, s0, 2); s1 += __shfl_xor_sync(0xffffffffu, s1, 2);
      s0 = __fdividef(1.0f, s0); s1 = __fdividef(1.0f, s1);
      pl[b][u] = pack2(a0 * rk[b][0] * s0, a1 * rk[b][1] * s0); ph[b][u] = pack2(b0 * rk[b][2] * s1, b1 * rk[b][3] * s1);
    }
  float O[2][2][4][4];
#pragma unroll
  for (int b = 1; b >= 0; b--)
#pragma unroll
    for (int u = 0; u < 2; u++)
#pragma unroll
      for (int nt = 0; nt < 4; nt++) {
        O[b][u][nt][0] = O[b][u][nt][1] = O[b][u][nt][2] = O[b][u][nt][3] = 0.f;
        mma16816(O[b][u][nt], pl[b][u] & ~mold, ph[b][u] & mold, 0u, ph[b][u] & ~mold, V[b][u * 4 + nt][0], V[b][u * 4 + nt][1]);
      }
#pragma unroll
  for (int b = 1; b >= 0; b--)
#pragma unroll
    for (int u = 0; u < 2; u++)
#pragma unroll
      for (int nt = 0; nt < 4; nt++) mma1688(O[b][u][nt], pl[b][u] & mold, 0u, HV[b][u * 4 + nt]);
  {
    uint32_t dep = 0;
#pragma unroll
    for (int i = 0; i < 16; i++) dep |= __float_as_uint(O[i >> 3][(i >> 2) & 1][i & 3][0]);
    bar_arrive(3 + wg + (dep & lds32(sbase + OFF_K01 + 4)), 256);
  }
  TRE(wg, l * 32 + 5);
  const int r7 = lane & 7;
#pragma unroll
  for (int b = 1; b >= 0; b--) {
    const uint32_t rb = slot0 + (b * 4 + wq) * 2048 + (((lane >> 3) & 1) * 8 + r7) * 128;
#pragma unroll
    for (int u = 0; u < 2; u++) {
      const float c0 = 1.f, c1 = 1.f;
#pragma unroll
      for (int np = 0; np < 2; np++)
        stmatrix4(rb + (((u * 4 + np * 2 + (lane >> 4)) ^ r7) << 4), pack2(O[b][u][2 * np][0] * c0, O[b][u][2 * np][1] * c0),
                  pack2(O[b][u][2 * np][2] * c1, O[b][u][2 * np][3] * c1), pack2(O[b][u][2 * np + 1][0] * c0, O[b][u][2 * np + 1][1] * c0),
                  pack2(O[b][u][2 * np + 1][2] * c1, O[b][u][2 * np + 1][3] * c1));
    }
  }
  fence_proxy_async_smem();
  __syncwarp();
  if (lane == 0) mbar_arrive(sbase + OFF_OST + wg * 8);
  TRE(wg, l * 32 + 6);
}

__device__ __forceinline__ uint4 ext_row(float mean) {
  const uint32_t hi = pack2(mean, mean);
  return make_uint4(hi, pack2(mean - bf_lo(hi), 0.f), 0, 0);
}
__device__ __forceinline__ uint4 ext_col(float cs) {
  cs *= -0.5f;
  const float hi = bf_lo(pack2(cs, 0.f));
  return make_uint4(pack2(hi, cs - hi), pack2(hi, 0.f), 0, 0);
}

template <int BN>
__device__ __forceinline__ void mixer_up(const Params& P, uint32_t sbase, Cons& c, int wg, int l) {
  float acc[2][BN / 2];
  {
    const uint32_t ba = sbase + OFF_B1 + (BN == 96 ? 256 : 0) + (opaque_tid() & 3) * 4;
#pragma unroll
    for (int j = 0; j < BN / 8; j++) {
      const uint32_t bv = lds32(ba + j * 16);
#pragma unroll
      for (int b = 0; b < 2; b++)
        asm volatile("shl.b32 %0, %4, 16;\n shl.b32 %2, %4, 16;\n and.b32 %1, %4, 0xffff0000;\n and.b32 %3, %4, 0xffff0000;"
                     : "=f"(acc[b][j * 4 + 0]), "=f"(acc[b][j * 4 + 1]), "=f"(acc[b][j * 4 + 2]), "=f"(acc[b][j * 4 + 3]) : "r"(bv));
    }
  }
  gemm_runs<2, BN, 1, 1, 4, 6, 0, 16384, 0, 16384, BN == 96 ? DP3B : DP3A>(P, sbase, c, acc, wg);
  TRE(wg, l * 32 + 16);
  if (BN == 96) mbar_wait(sbase + OFF_SFR, l);
  const int tid = opaque_tid(), lane = tid & 31, r7 = lane & 7;
  const uint32_t a0 = sbase + OFF_STG + (((tid >> 5) & 3) * 16 + ((lane >> 3) & 1) * 8 + r7) * 128;
  uint32_t sw[4];
#pragma unroll
  for (int k = 0; k < 4; k++) sw[k] = a0 + (((k * 2 + (lane >> 4)) ^ r7) << 4);
  float k01 = GELU_K01;
#pragma unroll
  for (int j = 0; j < BN / 16; j++) {
    if (j == 4) {
      fence_proxy_async_smem();
      __syncwarp();
      if (lane == 0) mbar_arrive(sbase + OFF_TU0 + wg * 8);
      k01 = __uint_as_float(lds32(sbase + OFF_K01));
    }
#pragma unroll
    for (int b = 0; b < 2; b++)
      stmatrix4(sw[j & 3] + b * 8192 + (j >> 2) * 16384, pack2(gelu_tanh(acc[b][j * 8 + 0], k01), gelu_tanh(acc[b][j * 8 + 1], k01)),
                pack2(gelu_tanh(acc[b][j * 8 + 2], k01), gelu_tanh(acc[b][j * 8 + 3], k01)),
                pack2(gelu_tanh(acc[b][j * 8 + 4], k01), gelu_tanh(acc[b][j * 8 + 5], k01)),
                pack2(gelu_tanh(acc[b][j * 8 + 6], k01), gelu_tanh(acc[b][j * 8 + 7], k01)));
  }
  fence_proxy_async_smem();
  __syncwarp();
  if (lane == 0) mbar_arrive(sbase + OFF_TU1 + wg * 8);
  TRE(wg, l * 32 + 17);
}

__device__ __forceinline__ void row_stats(const uint4 (&raw)[8], int row0, unsigned tag, int lane) {
  float s[2], q[2];
#pragma unroll
  for (int rr = 0; rr < 2; rr++) {
    s[rr] = 0.f; q[rr] = 0.f;
#pragma unroll
    for (int i = 0; i < 4; i++) {
      float v[8];
      unpack8(raw[rr * 4 + i], v);
      s[rr] += ((v[0] + v[1]) + (v[2] + v[3])) + ((v[4] + v[5]) + (v[6] + v[7]));
#pragma unroll
      for (int e = 0; e < 8; e++) q[rr] = fmaf(v[e], v[e], q[rr]);
    }
  }
#pragma unroll
  for (int o = 16; o > 0; o >>= 1)
#pragma unroll
    for (int rr = 0; rr < 2; rr++) { s[rr] += __shfl_xor_sync(0xffffffffu, s[rr], o); q[rr] += __shfl_xor_sync(0xffffffffu, q[rr], o); }
  const int row = row0 + (lane & 1);
  if (lane < 16)
    __stcg(&g_statsA[((row >> 6) * 8 + (lane >> 1)) * 64 + (row & 63)],
           make_uint4(__float_as_uint(((lane & 1) ? s[1] : s[0]) * 0.125f), tag, __float_as_uint(((lane & 1) ? q[1] : q[0]) * 0.125f), tag));
}
__device__ __forceinline__ uint4 ldg_v(const uint4* p) {
  uint4 v;
  asm volatile("ld.global.nc.v4.u32 {%0,%1,%2,%3}, [%4];" : "=r"(v.x), "=r"(v.y), "=r"(v.z), "=r"(v.w) : "l"(p) : "memory");
  return v;
}
__device__ __noinline__ void startup(const bf16* __restrict__ x, const bf16* __restrict__ wqkv, const bf16* __restrict__ b1,
                                     const bf16* __restrict__ b2, uint32_t sbase, unsigned tag, unsigned delay) {
  const int cta = LCTA, lane = threadIdx.x & 31, wq = __shfl_sync(0xffffffffu, (threadIdx.x >> 5) & 3, 0), m = cta >> 3, j = cta & 7;
  const int i = threadIdx.x & 127, row0 = cta * 8 + wq * 2;
  __nanosleep(delay);
  const uint4* xs = reinterpret_cast<const uint4*>(x + (size_t)row0 * D_DIM) + lane;
  const uint4* ws = reinterpret_cast<const uint4*>(wqkv + (size_t)(j * 128 + wq * 32 + (lane >> 3)) * (3 * D_DIM) + m * 64) + (lane & 7);
  uint4 raw[8], wr[8];
#pragma unroll
  for (int k = 0; k < 8; k++) raw[k] = ldg_v(xs + k * 32);
#pragma unroll
  for (int k = 0; k < 8; k++) wr[k] = ldg_v(ws + k * 4 * 384);
  if (wq < 3) __stcg(&g_cs[j * 1536 + m * 96 + i], make_uint4(0, 0, 0, 0));
  if (wq == 0) {
    if (lane < 28) {
      const int f = lane < 16 ? m * 128 + lane * 8 : 2048 + m * 96 + ((m & 1) ? (lane < 24 ? 32 + (lane - 16) * 8 : (lane - 24) * 8) : (lane - 16) * 8);
      float v[8];
      unpack8(*reinterpret_cast<const uint4*>(b1 + f), v);
#pragma unroll
      for (int e = 0; e < 8; e++) v[e] *= 0.5f;
      sts128(sbase + OFF_B1 + lane * 16, pack8(v));
    }
    if (lane < 16) sts128(sbase + OFF_B2 + lane * 16, *reinterpret_cast<const uint4*>(b2 + ((lane >> 3) * 16 + m) * 64 + (lane & 7) * 8));
  }
  const uint32_t sa = sbase + OFF_STG + 16384;
#define WAITFOR(v) if (v[7].x == tag + v[7].y * 65536 + 12345 && v[6].w == 99) delay++
#define COLSUM(v, p)                                                                                                          \
  {                                                                                                                           \
    float s[8];                                                                                                               \
    _Pragma("unroll") for (int e = 0; e < 8; e++) s[e] = 0.f;                                                                 \
    _Pragma("unroll") for (int k = 0; k < 8; k++) {                                                                           \
      float f[8];                                                                                                             \
      unpack8(v[k], f);                                                                                                       \
      _Pragma("unroll") for (int e = 0; e < 8; e++) s[e] += f[e];                                                             \
    }                                                                                                                         \
    const uint32_t a = sa + (wq * 4 + (lane >> 3)) * 768 + (p) * 256 + (lane & 7) * 32;                                       \
    sts128(a, make_uint4(__float_as_uint(s[0]), __float_as_uint(s[1]), __float_as_uint(s[2]), __float_as_uint(s[3])));       \
    sts128(a + 16, make_uint4(__float_as_uint(s[4]), __float_as_uint(s[5]), __float_as_uint(s[6]), __float_as_uint(s[7])));  \
  }
  uint4 w2[8];
  WAITFOR(raw);
#pragma unroll
  for (int k = 0; k < 8; k++) w2[k] = ldg_v(ws + 128 + k * 4 * 384 + (delay >> 31));
  row_stats(raw, row0, tag, lane);
  WAITFOR(wr);
#pragma unroll
  for (int k = 0; k < 8; k++) raw[k] = ldg_v(ws + 256 + k * 4 * 384 + (delay >> 31));
#pragma unroll 1
  for (int p = 0; p < 3; p++) {
    COLSUM(wr, p);
#pragma unroll
    for (int k = 0; k < 8; k++) { wr[k] = w2[k]; w2[k] = raw[k]; }
  }
  bar_sync(8, 128);
  if (wq < 3) {
    float a = 0.f, b = 0.f;
#pragma unroll
    for (int r = 0; r < 16; r++) { const float2 v = lds64f(sa + r * 768 + i * 8); a += v.x; b += v.y; }
    __stcg(&g_cs[j * 1536 + m * 96 + i], make_uint4(__float_as_uint(a), tag, __float_as_uint(b), tag));
  }
  TRE(1, 24);
#pragma unroll
  for (int k = 0; k < 8; k++) raw[k] = ldg_v(xs + 1024 * 128 + k * 32);
#pragma unroll 1
  for (int q = wq == 3 ? 0 : 1; q < 2; q++) {
    const int tk = q ? i : lane - 32;
    const int row = max(j * 128 + tk, 0);
    const uint4* p = &g_statsA[(row >> 6) * 512 + (row & 63)];
    uint4 v;
    for (int it = 0; it < (1 << 20); it++) {
      v = ld_volatile4(p);
      if (__all_sync(0xffffffffu, v.y == tag && v.w == tag)) break;
      __nanosleep(200);
    }
    const float mean = __uint_as_float(v.x) * (8.0f / D_DIM);
    const float rs = rsqrtf(fmaxf(fmaf(__uint_as_float(v.z), 8.0f / D_DIM, -mean * mean), 0.f) + 1e-5f);
    if (tk >= -16) sts32(sbase + OFF_ST + ((tk & 1) * 72 + 8 + (tk >> 1)) * 4, __float_as_uint(rs));
    if (q) sts128(sbase + OFF_STG + ((i & 64) + (i & 1) * 32 + ((i & 63) >> 1)) * 16, ext_row(mean));
  }
  if (wq < 3) {
    const uint4* p = &g_cs[m * 96 + i];
    uint4 v[8];
    for (int it = 0; it < (1 << 20); it++) {
      bool ok = true;
#pragma unroll
      for (int r = 0; r < 8; r++) v[r] = ld_volatile4(p + r * 1536);
#pragma unroll
      for (int r = 0; r < 8; r++) ok = ok && v[r].y == tag && v[r].w == tag;
      if (__all_sync(0xffffffffu, ok)) break;
      __nanosleep(100);
    }
    float a = 0.f, b = 0.f;
#pragma unroll
    for (int r = 0; r < 8; r++) { a += __uint_as_float(v[r].x); b += __uint_as_float(v[r].z); }
    sts64f(sbase + OFF_CS + i * 8, a, b);
    sts128(sbase + OFF_STG + 2048 + i * 32, ext_col(a));
    sts128(sbase + OFF_STG + 2048 + i * 32 + 16, ext_col(b));
  }
  fence_proxy_async_smem();
  bar_sync(8, 128);
  if (i == 0) mbar_arrive(sbase + OFF_STR);
  TRE(1, 27);
  row_stats(raw, row0 + 1024, tag, lane);
  __syncwarp();
}

__device__ __forceinline__ void poll8(uint4 (&v)[8], const uint4* p, int stride, unsigned tag) {
#pragma unroll 1
  for (int it = 0; it < (1 << 20); it++) {
    bool ok = true;
#pragma unroll
    for (int i = 0; i < 8; i++) v[i] = ld_volatile4(p + i * stride);
#pragma unroll
    for (int i = 0; i < 8; i++) ok = ok && v[i].y == tag && v[i].w == tag;
    if (SKEL || __all_sync(0xffffffffu, ok)) break;
    __nanosleep(200);
  }
}

__global__ void __launch_bounds__(384, 1)
mega_kernel(const __grid_constant__ Params P, const bf16* __restrict__ x, const bf16* __restrict__ wqkv, const bf16* __restrict__ b1,
            const bf16* __restrict__ b2) {
  extern __shared__ __align__(1024) uint8_t smem_raw[];
  const uint32_t sbase = smem_u32(smem_raw);
  if (threadIdx.x == 0) sts128(sbase + OFF_K01, make_uint4(__float_as_uint(GELU_K01), 0, logical_cta(P.map), 0));
  if (threadIdx.x == 256) {
    for (int s = 0; s < 32; s++) mbar_init(sbase + OFF_FULL + s * 8, 2);
    for (int w = 0; w < 2; w++) {
      mbar_init(sbase + OFF_STR + w * 8, 1);
      mbar_init(sbase + OFF_OST + w * 8, 4); mbar_init(sbase + OFF_TR + w * 8, 4);
      mbar_init(sbase + OFF_TU0 + w * 8, 4); mbar_init(sbase + OFF_TU1 + w * 8, 4);
    }
    mbar_init(sbase + OFF_SFR, 1);
    for (int s = 0; s < 10; s++) mbar_init(sbase + OFF_DEP + s * 8, 1);
    asm volatile("fence.mbarrier_init.release.cluster;" ::: "memory");
  }
  __syncthreads();

  if (LCTA < 0) {
    if (threadIdx.x == 0) {
      const unsigned epoch = *(volatile unsigned*)&g_epoch;
      for (int it = 0; it < (1 << 20) && (int)(*(volatile unsigned*)&g_sync[2] - (epoch * 9 + 1) * NCTA) < 0; it++) __nanosleep(2000);
    }
    return;
  }
  const int warp = __shfl_sync(0xffffffffu, threadIdx.x >> 5, 0);
  const int wg = warp >> 2;
  if (wg == 2) {
    asm volatile("setmaxnreg.dec.sync.aligned.u32 %0;" ::"n"(RLO));
    if (warp == 8) {
      producer<0>(P, sbase);
    } else if (warp == 9) {
      producer<1>(P, sbase);
    } else {
      const unsigned epoch = *(volatile unsigned*)&g_epoch;
      const int cta = LCTA, lane = threadIdx.x & 31, w = warp - 10, m = cta >> 3, j = cta & 7;
      unsigned* const cn = &g_sync[2 + w];
      unsigned tgt = epoch * (9 - 2 * w) * NCTA;
      if (w == 1 && lane < 19) prefetch_tmap(reinterpret_cast<const CUtensorMap*>(&P) + lane);
#pragma unroll 1
      for (int l = 0; l < 2; l++) {
        const unsigned tag = epoch * 2 + l + 1;
        if (w == 1) mbar_wait(sbase + OFF_OST, l);
        else if (l) mbar_wait(sbase + OFF_OST + 8, 0);
        if (w | l) {
          const uint32_t ea = sbase + OFF_STG + w * 16384;
#pragma unroll 1
          for (int r = 0; r < 6; r++) sts128(ea + 2048 + (r * 32 + lane) * 16, ext_col(__uint_as_float(lds32(sbase + OFF_CS + (r * 32 + lane) * 4))));
#pragma unroll 1
          for (int tk = lane - 32; tk < 128; tk += 32) {
            const int row = max((w * 8 + j) * 128 + tk, 0);
            uint4 v[8];
            poll8(v, &g_statsA[(row >> 6) * 512 + (row & 63)], 64, tag);
            float mean = 0.f, var = 0.f;
#pragma unroll
            for (int i = 0; i < 8; i++) { mean += __uint_as_float(v[i].x); var += __uint_as_float(v[i].z); }
            mean *= (1.0f / D_DIM);
            const float rs = rsqrtf(fmaxf(fmaf(var, 1.0f / D_DIM, -mean * mean), 0.f) + 1e-5f);
            if (tk >= -16) sts32(sbase + OFF_ST + ((tk & 1) * 72 + 8 + (tk >> 1)) * 4, __float_as_uint(rs));
            if (tk >= 0) sts128(ea + ((tk & 64) + (tk & 1) * 32 + ((tk & 63) >> 1)) * 16, ext_row(mean));
          }
          fence_proxy_async_smem();
        }
        __syncwarp();
        if (lane == 0) {
          const uint32_t stg = sbase + OFF_STG;
#define PUBLISH(ev, t1)        \
  red_release(cn);             \
  TRA(w, l * 32 + (t1));       \
  spin_until(cn, tgt += NCTA); \
  mbar_arrive(sbase + OFF_DEP + (ev) * 8)
          if (w | l) mbar_arrive(sbase + OFF_STR + w * 8);
          TRA(w, l * 32 + 8);
          mbar_wait(sbase + OFF_OST + w * 8, l);
          tma_store(&P.o_s, stg + w * 16384, m * 64, 0, 0, w * 16 + j * 2);
          bulk_commit();
          bulk_wait<0>();
          TRA(w, l * 32 + 7);
          PUBLISH(E_O + w, 9);
          mbar_wait(sbase + OFF_TR + w * 8, 0);
          tma_store(&P.h_m, stg + w * 16384, j * 128, (w * 16 + m) * 64, 0, 0);
          bulk_commit();
          bulk_wait<0>();
          TRA(w, l * 32 + 14);
          PUBLISH(E_H + w, 15);
          const int f0 = w ? 2048 + m * 96 + (m & 1) * 32 : m * 128;
          mbar_wait(sbase + OFF_TU0 + w * 8, l);
          TRA(w, l * 32 + 25);
          if (w == 0) {
            tma_store(&P.u_k, stg, f0, j * 128, 0, 0);
            bulk_commit();
            bulk_wait<0>();
            TRA(w, l * 32 + 26);
            red_release(cn);
            TRA(w, l * 32 + 18);
            mbar_wait(sbase + OFF_TU1, l);
            tma_store(&P.u_k, stg + 16384, f0 + 64, j * 128, 0, 0);
            bulk_commit();
            spin_until(cn, tgt += NCTA);
            mbar_arrive(sbase + OFF_DEP + E_UA * 8);
            bulk_wait<0>();
            mbar_arrive(sbase + OFF_SFR);
          } else {
            __nanosleep(P.u1d);
#pragma unroll 1
            for (int pc = 0; pc < 256 / PROWS; pc++) {
              if (pc == 128 / PROWS) mbar_wait(sbase + OFF_TU1 + 8, l);
              if (pc < 128 / PROWS) tma_store(&P.u_s, stg + pc * PROWS * 128, f0, j * 128 + pc * PROWS, 0, 0);
              else tma_store(&P.u_h, stg + pc * PROWS * 128, 0, j * 128 + pc * PROWS - 128, 64 + m * 3 + 2 - (m & 1) * 2, 0);
              bulk_commit();
              bulk_wait_read<PACE>();
            }
            bulk_wait<0>();
          }
          PUBLISH(E_UB + w, 19);
          if (l == 0) {
            mbar_wait(sbase + OFF_TR + w * 8, 1);
            tma_store(&P.x2m, stg + w * 16384, j * 128, (w * 16 + m) * 64, 0, 0);
            bulk_commit();
            bulk_wait<0>();
            TRA(w, l * 32 + 28);
            PUBLISH(E_X + w, 23);
          }
        }
        __syncwarp();
      }
    }
  } else {
    asm volatile("setmaxnreg.inc.sync.aligned.u32 %0;" ::"n"(RHI));
    TRE(wg, 63);
    TRG(wg, 63);
    const unsigned epoch = *(volatile unsigned*)&g_epoch;
    if (wg == 1) startup(x, wqkv, b1, b2, sbase, epoch * 2 + 1, P.sud);
    Cons c;
    c.nsolo = 0; c.nshr = 0; c.ri = 0;
#pragma unroll 1
    for (int l = 0; l < 2; l++) {
      {
        float acc[2][96];
#pragma unroll
        for (int b = 0; b < 2; b++)
#pragma unroll
          for (int i = 0; i < 96; i++) acc[b][i] = 0.f;
        gemm_runs<2, 192, 0, 1, 6, 6, 0, 16384, 0, 0, 1>(P, sbase, c, acc, wg);
        attention(P, acc, sbase, c, wg, l, epoch * 2 + l + 1);
      }
      uint32_t xr[32];
      {
        float acc[1][64];
        {
          if (PREW) {
            const int cta = opaque_cta(), tid = opaque_tid();
            if ((tid & 3) < 2) __stcg(&g_statsB[(wg * 16 + (cta >> 3)) * 512 + (cta & 7) * 64 + ((tid >> 5) & 3) * 16 + ((tid & 31) >> 2) + (tid & 3) * 8], make_uint4(0, 0, 0, 0));
          }
          const uint32_t r = P.run[wg][c.ri];
          c.ri++;
          mbar_wait(sbase + OFF_FULL + wg * 64 + (c.nsolo & 7) * 8, (c.nsolo >> 3) & 1);
          c.nsolo++;
          const int tid = opaque_tid(), lane = tid & 31, r7 = lane & 7;
          const uint32_t sa = sbase + ((r >> 6) & 31) * 8192 + (((tid >> 5) & 3) * 16 + ((lane >> 3) & 1) * 8 + r7) * 128;
#pragma unroll
          for (int j = 0; j < 8; j++) {
            uint32_t q[4];
            ldmatrix4(q, sa + (j >> 2) * 8192 + ((((j * 2 + (lane >> 4)) & 7) ^ r7) << 4));
#pragma unroll
            for (int i = 0; i < 4; i++) { acc[0][j * 8 + i * 2] = bf_lo(q[i]); acc[0][j * 8 + i * 2 + 1] = bf_hi(q[i]); }
          }
          bar_sync(7 + wg, 128);
          if ((tid & 127) == 0) mbar_arrive_n(sbase + OFF_EMPTY + ((r >> 11) & 7) * 8, 2);
        }
        gemm_runs<1, 128, 0, 1, 3, 3, 16384, 0, 0, 0, DP2>(P, sbase, c, acc, wg);
        TRE(wg, l * 32 + 10);
        const int cta = opaque_cta(), tid = opaque_tid(), lane = tid & 31, rw = ((tid >> 5) & 3) * 16;
        const unsigned tag = epoch * 2 + l + 1;
        uint4* sb = &g_statsB[(wg * 16 + (cta >> 3)) * 512 + rw];
        tile_stats(acc[0], sb + (cta & 7) * 64 + (lane >> 2), tag, lane & 3);
        TRE(wg, l * 32 + 11);
#pragma unroll
        for (int j = 0; j < 16; j++) {
          xr[j * 2] = pack2(acc[0][j * 4 + 0], acc[0][j * 4 + 1]);
          xr[j * 2 + 1] = pack2(acc[0][j * 4 + 2], acc[0][j * 4 + 3]);
        }
        const uint4* sp = sb + (lane & 1) * 256 + (lane >> 1);
        uint4 a, b, cc, d;
        int it = 0;
        __nanosleep(P.pre);
        while (true) {
          a = ld_volatile4(sp); b = ld_volatile4(sp + 64); cc = ld_volatile4(sp + 128); d = ld_volatile4(sp + 192);
          bool ok = a.y == tag && a.w == tag && b.y == tag && b.w == tag && cc.y == tag && cc.w == tag && d.y == tag && d.w == tag;
          if (SKEL || ok || ++it > (1 << 20)) break;
          __nanosleep(P.poll);
        }
        __syncwarp();
        TRE(wg, l * 32 + 12);
        float mean = (__uint_as_float(a.x) + __uint_as_float(b.x)) + (__uint_as_float(cc.x) + __uint_as_float(d.x));
        float v = (__uint_as_float(a.z) + __uint_as_float(b.z)) + (__uint_as_float(cc.z) + __uint_as_float(d.z));
        mean += __shfl_xor_sync(0xffffffffu, mean, 1);
        v += __shfl_xor_sync(0xffffffffu, v, 1);
        mean *= (1.0f / D_DIM);
        v = fmaxf(fmaf(v, 1.0f / D_DIM, -mean * mean), 0.f);
        const float rs = 0.5f * rsqrtf(fmaf(v + 1e-5f, 1e-5f, v));
        mean *= -rs;
        const int g2 = (lane >> 2) * 2;
        const float nm0 = __shfl_sync(0xffffffffu, mean, g2), rs0 = __shfl_sync(0xffffffffu, rs, g2);
        const float nm1 = __shfl_sync(0xffffffffu, mean, g2 + 16), rs1 = __shfl_sync(0xffffffffu, rs, g2 + 16);
        uint32_t hk[32];
#pragma unroll
        for (int j = 0; j < 16; j++) {
          hk[j * 2] = pack2(fmaf(acc[0][j * 4 + 0], rs0, nm0), fmaf(acc[0][j * 4 + 1], rs0, nm0));
          hk[j * 2 + 1] = pack2(fmaf(acc[0][j * 4 + 2], rs1, nm1), fmaf(acc[0][j * 4 + 3], rs1, nm1));
        }
        stage_tile128(hk, sbase + OFF_STG + wg * 16384 + rw * 128, lane);
        TRE(wg, l * 32 + 13);
        fence_proxy_async_smem();
        __syncwarp();
        if (lane == 0) mbar_arrive(sbase + OFF_TR + wg * 8);
      }
      if (wg == 0) mixer_up<128>(P, sbase, c, 0, l);
      else mixer_up<96>(P, sbase, c, 1, l);
      {
        float acc[1][64];
        {
          const int tid = opaque_tid();
          uint16_t bb0, bb1;
          const uint32_t ba = sbase + OFF_B2 + ((tid >> 5) * 16 + ((tid & 31) >> 2)) * 2;
          asm volatile("ld.shared.u16 %0, [%1];" : "=h"(bb0) : "r"(ba) : "memory");
          asm volatile("ld.shared.u16 %0, [%1];" : "=h"(bb1) : "r"(ba + 16) : "memory");
          const float bias0 = __uint_as_float((uint32_t)bb0 << 16), bias1 = __uint_as_float((uint32_t)bb1 << 16);
#pragma unroll
          for (int j = 0; j < 16; j++) {
            acc[0][j * 4 + 0] = bf_lo(xr[j * 2]) + bias0; acc[0][j * 4 + 1] = bf_hi(xr[j * 2]) + bias0;
            acc[0][j * 4 + 2] = bf_lo(xr[j * 2 + 1]) + bias1; acc[0][j * 4 + 3] = bf_hi(xr[j * 2 + 1]) + bias1;
          }
        }
        gemm_runs<1, 128, 1, 0, 3, 4, 16384, 0, 8192, 0, DP4>(P, sbase, c, acc, wg);
        TRE(wg, l * 32 + 20);
        const int cta = opaque_cta(), tid = opaque_tid(), lane = tid & 31, rw = ((tid >> 5) & 3) * 16;
#pragma unroll
        for (int j = 0; j < 16; j++) {
          xr[j * 2] = pack2(acc[0][j * 4 + 0], acc[0][j * 4 + 1]);
          xr[j * 2 + 1] = pack2(acc[0][j * 4 + 2], acc[0][j * 4 + 3]);
        }
        const uint32_t src = sbase + OFF_STG + wg * 16384 + rw * 128;
        stage_tile128(xr, src, lane);
        TRE(wg, l * 32 + 21);
        if (l) store_rows(&P.out_s, src, (cta & 7) * 128, (wg * 16 + (cta >> 3)) * 64 + rw, 0, lane);
        else {
          fence_proxy_async_smem();
          __syncwarp();
          if (lane == 0) mbar_arrive(sbase + OFF_TR + wg * 8);
        }
        if (l == 0) tile_stats(acc[0], &g_statsA[(wg * 16 + (cta >> 3)) * 512 + (cta & 7) * 64 + rw + (lane >> 2)], epoch * 2 + 2, lane & 3);
        TRE(wg, l * 32 + 22);
      }
    }
    TRE(wg, 62);
    TRG(wg, 62);
    if ((threadIdx.x & 127) == 0) {
      const unsigned v = atomicAdd(&g_exit, 1);
      if (v == (epoch + 1) * 2 * NCTA - 1) { __threadfence(); *(volatile unsigned*)&g_epoch = epoch + 1; }
    }
  }
}

typedef CUresult (*PFN_encodeTiled)(CUtensorMap*, CUtensorMapDataType, cuuint32_t, void*, const cuuint64_t*,
                                    const cuuint64_t*, const cuuint32_t*, const cuuint32_t*, CUtensorMapInterleave,
                                    CUtensorMapSwizzle, CUtensorMapL2promotion, CUtensorMapFloatOOBfill);
static PFN_encodeTiled g_encode = nullptr;

static CUtensorMap make_map4(const void* ptr, int d0, int d1, int d2, int d3, int s1, int s2, int s3, int b1, int b2, int b3) {
  CUtensorMap m;
  cuuint64_t dims[4] = {(cuuint64_t)d0, (cuuint64_t)d1, (cuuint64_t)d2, (cuuint64_t)d3};
  cuuint64_t strides[3] = {(cuuint64_t)s1 * 2, (cuuint64_t)s2 * 2, (cuuint64_t)s3 * 2};
  cuuint32_t box[4] = {64, (cuuint32_t)b1, (cuuint32_t)b2, (cuuint32_t)b3};
  cuuint32_t es[4] = {1, 1, 1, 1};
  g_encode(&m, CU_TENSOR_MAP_DATA_TYPE_BFLOAT16, 4, (void*)ptr, dims, strides, box, es, CU_TENSOR_MAP_INTERLEAVE_NONE,
           CU_TENSOR_MAP_SWIZZLE_128B, CU_TENSOR_MAP_L2_PROMOTION_L2_128B, CU_TENSOR_MAP_FLOAT_OOB_FILL_NONE);
  return m;
}
static CUtensorMap make_map(const void* ptr, int rows, int cols, int box_rows, int nblk = 1, int bstep = 64) {
  return make_map4(ptr, cols - (nblk - 1) * bstep, rows, nblk, 1, cols, bstep, 64, box_rows, nblk, 1);
}

#define tune(n, d) (d)
#define PX tune("PX", 8)
#define PA1 tune("PA1", 1)
#define PY tune("PY", 11)
#define PB1 tune("PB1", 2)
#define PZ tune("PZ", 10)
#define PV tune("PV", 4)
#define PA4 tune("PA4", 12)

struct Sched {
  Params& P;
  int pos = 0, e = 0, nr[2] = {0, 0}, l = 0;
  int cap[12] = {8, 8, 8, 8, tune("C2", 8), tune("C2", 8), 8, tune("C3", 8), 8, tune("C4", 8), tune("C4", 8), 8};
  int freeu = RING_U, tail = 0, used[512], cnt[3] = {0, 0, 0};
  Sched(Params& p) : P(p) { P.nseg = 0; }
  void pf(int back, int kind, int k0, int n, int ks = 1) {
    static const int size[12] = {6, 6, 3, 3, 3, 3, 4, 4, 6, 3, 3, 4};
    if (n <= 0) return;
    const uint2 d = make_uint2(kind | k0 << 4 | n << 10 | (ks - 1) << 16 | 1u << 28, 0), o = P.seg[P.nseg - 1];
    const int on = (o.x >> 10) & 63, at = on - back;
    if (back <= 0) { P.seg[P.nseg++] = d; return; }
    if (at <= 0) { P.seg[P.nseg - 1] = d; P.seg[P.nseg++] = o; return; }
    P.seg[P.nseg - 1].x -= back << 10;
    P.seg[P.nseg++] = d;
    uint32_t wc = 0;
    for (int i = 0; i < 14 && i < back; i++) wc |= (at + i < 14 ? (o.y >> (2 * (at + i))) & 3 : 1) << (2 * i);
    P.seg[P.nseg++] = make_uint2((o.x & 0x0801000f) | (((o.x >> 4) & 63) + at * (((o.x >> 16) & 1) + 1)) << 4 | back << 10 |
                                 (((o.x >> 22) & 31) + at * size[o.x & 15]) % RING_U << 22, wc | (((o.y >> 29) + at) & 7) << 29);
  }
  void add(int kind, int k0, int n, int dep, int pre, int post, int fl, int ks = 1) {
    if (n <= 0) return;
    static const int size[12] = {6, 6, 3, 3, 3, 3, 4, 4, 6, 3, 3, 4};
    const int sz = size[kind], sh = kind == K_G3S || kind == K_G4S, w = (kind < K_G3S ? kind : kind - 1) & 1, set = sh ? 2 : w;
    int pad = (pos + sz - 1) / sz * sz - pos;
    pos = (pos + pad) % RING_U;
    for (int v = 0; v < 2; v++)
      if (sh || v == w) {
        const int last = ((fl >> (2 + v)) & 1) | (fl >> 4), drain = ((fl >> v) & 1) | ((fl >> (2 + v)) & 1);
        P.run[v][nr[v]++] = n | pos << 6 | (e & 7) << 11 | sh << 14 | (sh && !v ? 0 : pre) << 15 | (sh && v ? 0 : post) << 19 | drain << 23 | last << 24;
      }
    int i0 = 0;
    const uint32_t px = P.nseg ? P.seg[P.nseg - 1].x : ~0u;
    if (!(px >> 28) && (int)(px & 15) == kind && !dep && (int)((px >> 16) & 1) == ks - 1 && (int)(((px >> 4) & 63) + ((px >> 10) & 63) * ks) == k0) {
      i0 = (px >> 10) & 63;
      P.seg[P.nseg - 1].x += n << 10;
    } else P.seg[P.nseg++] = make_uint2(kind | k0 << 4 | n << 10 | (ks - 1) << 16 | dep << 17 | pos << 22 | l << 27, (cnt[set] & 7) << 29);
    for (int i = i0; i < i0 + n; i++) {
      int nw = 0;
      while (freeu < sz + pad || e - tail >= cap[kind]) { freeu += used[tail++]; nw++; }
      if (i >= 14 && nw == 0) { freeu += used[tail++]; nw++; }
      if (nw > 3 || (i >= 14 && nw != 1)) P.nseg = -1000000;
      if (i < 14) P.seg[P.nseg - 1].y |= nw << (2 * i);
      freeu -= used[e++] = sz + pad;
      pad = 0;
    }
    pos = (pos + n * sz) % RING_U;
    cnt[set] += n;
  }
};

static void build_schedule(Params& P) {
  Sched s(P);
  P.map = tune("MAP", 0);
  P.u1d = tune("U1D", 0);
  P.sud = tune("SUD", 500);
  P.pre = tune("PRE", 150);
  P.poll = tune("POLL", 40);
  const int pfm = tune("PFM", 0), sk3 = tune("SK3", 3), sk4 = tune("SK4", 5);
  for (int l = 0; l < 2; l++) {
    s.l = l;
    const int b = l * 16, a4 = l ? tune("PA4L", 8) : PA4;
    s.add(K_G1, 0, 13, l ? E_X : 0, 0, 0, 16);
    s.add(K_G1, 13, 3, 0, 0, 1, 0);
    s.add(K_G1 + 1, 0, PA1, l ? E_X + 1 : 0, 1, 0, 3);
    s.add(K_G1 + 1, PA1, PX - PA1, 0, 3, 0, 3);
    if (pfm & 16) s.pf(5, K_G2, 0, 16);
    s.add(K_RES, 0, 1, 0, 0, 0, 0);
    s.add(K_G2, 0, 16, b + E_O, 0, 1, 12);
    s.add(K_G1 + 1, PX, 13 - PX, 0, 1, 0, 16);
    s.add(K_G1 + 1, 13, 3, 0, 0, PB1 ? 2 : 0, 0);
    s.add(K_G3, 0, PB1, b + E_H, 2, 0, 3);
    s.add(K_G3, PB1, PY - PB1, PB1 ? 0 : b + E_H, 4, 0, 3);
    if (pfm & 8) { s.pf(6, K_G3 + 1, 0, 8); s.pf(2, K_G3 + 1, 8, PZ - 8); }
    s.add(K_RES + 1, 0, 1, 0, 0, 0, 0);
    s.add(K_G2 + 1, 0, 16, b + E_O + 1, 0, 2, 12);
    s.add(K_G3, PY, 16 - PY, 0, 2, 0, 3);
    s.add(K_G3 + 1, 0, PZ, 0, 0, 0, 3);
    s.add(K_G3, 16, PV, b + E_H + 1, 0, 0, 0);
    s.add(K_G3S, 16 + PV, 16 - PV - sk3, PV ? 0 : b + E_H + 1, 0, 0, sk3 ? 2 : 4);
    s.add(K_G3S, 32 - sk3, sk3, 0, 1, 1, 4);
    if (pfm & 1) { s.pf(7, K_G3 + 1, PZ, 8); s.pf(4, K_G3 + 1, PZ + 8, 8 + PV - PZ); }
    if (pfm & 2) s.pf(1, K_G4, 0, 8, 2);
    s.add(K_G3 + 1, PZ, 16 + PV - PZ, 0, 0, 2, 12);
    if (pfm & 2) s.pf(8, K_G4, 16, a4 - 8, 2);
    s.add(K_G4, 0, a4, b + E_UA, 2, 0, 0, 2);
    s.add(K_G4S, a4 * 2, 16 - a4, 0, 0, 0, 0, 2);
    s.add(K_G4S, 1, 16, b + E_UB, 0, 0, 0, 2);
    s.add(K_G4S, 32, 24 - sk4, b + E_U1, 0, 0, sk4 ? 2 : 4);
    s.add(K_G4S, 56 - sk4, sk4, 0, 1, 1, 4);
    if (pfm & 4) { s.pf(12, K_G4 + 1, 0, 8, 2); s.pf(6, K_G4 + 1, 16, a4 - 8, 2); }
    s.add(K_G4 + 1, 0, a4, 0, 0, 0, 12, 2);
  }
}

extern "C" void kernel_launch(void* const* d_in, const int* in_sizes, int n_in, void* d_out, int out_size) {
  const bf16* x = (const bf16*)d_in[0];
  const bf16* wqkv = (const bf16*)d_in[1];
  const bf16* wo = (const bf16*)d_in[2];
  const bf16* w1 = (const bf16*)d_in[4];
  const bf16* b1 = (const bf16*)d_in[5];
  const bf16* w2 = (const bf16*)d_in[6];
  const bf16* b2 = (const bf16*)d_in[7];
  bf16* out = (bf16*)d_out;

  if (!g_encode) {
    void* fn = nullptr;
    cudaDriverEntryPointQueryResult st;
    cudaGetDriverEntryPoint("cuTensorMapEncodeTiled", &fn, cudaEnableDefault, &st);
    g_encode = (PFN_encodeTiled)fn;
  }
  bf16 *h, *o, *u, *x2;
  cudaGetSymbolAddress((void**)&h, g_h);
  cudaGetSymbolAddress((void**)&o, g_o);
  cudaGetSymbolAddress((void**)&u, g_u);
  cudaGetSymbolAddress((void**)&x2, g_x2);
  Params P;
  P.xq[0] = make_map4(x, D_DIM, 32, 2, 32, 2 * D_DIM, D_DIM, 64 * D_DIM, 32, 2, 2);
  P.xq[1] = make_map4(x2, D_DIM, 32, 2, 32, 2 * D_DIM, D_DIM, 64 * D_DIM, 32, 2, 2);
  P.o_s = make_map4(o, D_DIM, 32, 2, 32, 2 * D_DIM, D_DIM, 64 * D_DIM, 32, 2, 2);
  P.xr[0] = make_map(x, S_LEN, D_DIM, 64);
  P.xr[1] = make_map(x2, S_LEN, D_DIM, 64);
  P.x2m = make_map(x2, S_LEN, D_DIM, 64, 2);
  P.wqkv = make_map(wqkv, D_DIM, 3 * D_DIM, 64, 3, 1024);
  P.o_k = make_map(o, S_LEN, D_DIM, 64);
  P.wo = make_map(wo, D_DIM, D_DIM, 64, 2);
  P.h_m = make_map(h, S_LEN, D_DIM, 64, 2);
  P.w1a = make_map(w1, S_LEN, F_DIM, 64, 2);
  P.w1b = make_map(w1, S_LEN, F_DIM, 64);
  P.w2s = make_map(w2, F_DIM, S_LEN, 64);
  P.w2d = make_map(w2, F_DIM, S_LEN, 64, 2, 1024);
  P.u_k = make_map(u, D_DIM, F_DIM, 128);
  P.u_s = make_map(u, D_DIM, F_DIM, PROWS);
  P.w1h = make_map4(w1, 32, S_LEN, F_DIM / 32, 1, F_DIM, 32, 64, 64, 1, 1);
  P.u_h = make_map4(u, 32, D_DIM, F_DIM / 32, 1, F_DIM, 32, 64, PROWS, 1, 1);
  P.out_s = make_map(out, S_LEN, D_DIM, 16);
  build_schedule(P);
  cudaFuncSetAttribute(mega_kernel, cudaFuncAttributeMaxDynamicSharedMemorySize, SMEM_TOTAL);
  int sms = 0;
  cudaDeviceGetAttribute(&sms, cudaDevAttrMultiProcessorCount, 0);
  mega_kernel<<<sms == 132 && tune("G132", 1) ? 132 : NCTA, 384, SMEM_TOTAL, cudaStreamPerThread>>>(P, x, wqkv, b1, b2);
}
```

```cpp
#include <cuda_runtime.h>
#include <cuda_bf16.h>
#include <cuda.h>
#include <stdint.h>

typedef __nv_bfloat16 bf16;

#define S_LEN 2048
#define D_DIM 1024
#define F_DIM 3584
#define NCTA 128

__device__ __forceinline__ uint32_t smem_u32(const void* p) { return (uint32_t)__cvta_generic_to_shared(p); }
__device__ __forceinline__ void mbar_init(uint32_t bar, uint32_t count) {
  asm volatile("mbarrier.init.shared::cta.b64 [%0], %1;" ::"r"(bar), "r"(count) : "memory");
}
__device__ __forceinline__ void mbar_arrive(uint32_t bar) {
  asm volatile("mbarrier.arrive.shared::cta.b64 _, [%0];" ::"r"(bar) : "memory");
}
__device__ __forceinline__ void mbar_arrive_n(uint32_t bar, uint32_t n) {
  asm volatile("mbarrier.arrive.shared::cta.b64 _, [%0], %1;" ::"r"(bar), "r"(n) : "memory");
}
__device__ __forceinline__ void mbar_wait(uint32_t bar, uint32_t parity) {
  asm volatile(
      "{\n.reg .pred p;\n.reg .u32 c;\nmov.u32 c, 0;\n"
      "WAIT_LOOP:\n"
      "mbarrier.try_wait.parity.shared::cta.b64 p, [%0], %1;\n"
      "@p bra.uni WAIT_DONE;\n"
      "add.u32 c, c, 1;\n"
      "setp.lt.u32 p, c, 4194304;\n"
      "@p bra.uni WAIT_LOOP;\n"
      "trap;\n"
      "WAIT_DONE:\n}\n" ::"r"(bar), "r"(parity) : "memory");
}
__device__ __forceinline__ void prefetch_tmap(const CUtensorMap* tm) {
  asm volatile("prefetch.tensormap [%0];" ::"l"((uint64_t)tm) : "memory");
}
__device__ __forceinline__ void wgmma_fence() { asm volatile("wgmma.fence.sync.aligned;" ::: "memory"); }
__device__ __forceinline__ void wgmma_commit() { asm volatile("wgmma.commit_group.sync.aligned;" ::: "memory"); }
template <int N>
__device__ __forceinline__ void wgmma_wait() { asm volatile("wgmma.wait_group.sync.aligned %0;" ::"n"(N) : "memory"); }
__device__ __forceinline__ void bar_sync(int id, int nthreads) { asm volatile("bar.sync %0, %1;" ::"r"(id), "r"(nthreads) : "memory"); }
__device__ __forceinline__ void bar_arrive(int id, int nthreads) { asm volatile("bar.arrive %0, %1;" ::"r"(id), "r"(nthreads) : "memory"); }
__device__ __forceinline__ uint64_t make_desc(uint32_t addr, uint32_t lbo_bytes, uint32_t sbo_bytes) {
  uint64_t d = 0;
  d |= (uint64_t)((addr & 0x3FFFF) >> 4);
  d |= (uint64_t)((lbo_bytes & 0x3FFFF) >> 4) << 16;
  d |= (uint64_t)((sbo_bytes & 0x3FFFF) >> 4) << 32;
  d |= (uint64_t)1 << 62;
  return d;
}
template<int TA, int TB>
__device__ __forceinline__ void wgmma_n64(float (&d)[32], uint64_t da, uint64_t db, int scaleD) {
  asm volatile("{\n.reg .pred p;\nsetp.ne.b32 p, %34, 0;\n"
    "wgmma.mma_async.sync.aligned.m64n64k16.f32.bf16.bf16 {%0, %1, %2, %3, %4, %5, %6, %7, %8, %9, %10, %11, %12, %13, %14, %15, %16, %17, %18, %19, %20, %21, %22, %23, %24, %25, %26, %27, %28, %29, %30, %31}, %32, %33, p, 1, 1, %35, %36;\n}\n"
    : "+f"(d[0]), "+f"(d[1]), "+f"(d[2]), "+f"(d[3]), "+f"(d[4]), "+f"(d[5]), "+f"(d[6]), "+f"(d[7]), "+f"(d[8]), "+f"(d[9]), "+f"(d[10]), "+f"(d[11]), "+f"(d[12]), "+f"(d[13]), "+f"(d[14]), "+f"(d[15]), "+f"(d[16]), "+f"(d[17]), "+f"(d[18]), "+f"(d[19]), "+f"(d[20]), "+f"(d[21]), "+f"(d[22]), "+f"(d[23]), "+f"(d[24]), "+f"(d[25]), "+f"(d[26]), "+f"(d[27]), "+f"(d[28]), "+f"(d[29]), "+f"(d[30]), "+f"(d[31])
    : "l"(da), "l"(db), "r"(scaleD), "n"(TA), "n"(TB));
}

template<int TA, int TB>
__device__ __forceinline__ void wgmma_n96(float (&d)[48], uint64_t da, uint64_t db, int scaleD) {
  asm volatile("{\n.reg .pred p;\nsetp.ne.b32 p, %50, 0;\n"
    "wgmma.mma_async.sync.aligned.m64n96k16.f32.bf16.bf16 {%0, %1, %2, %3, %4, %5, %6, %7, %8, %9, %10, %11, %12, %13, %14, %15, %16, %17, %18, %19, %20, %21, %22, %23, %24, %25, %26, %27, %28, %29, %30, %31, %32, %33, %34, %35, %36, %37, %38, %39, %40, %41, %42, %43, %44, %45, %46, %47}, %48, %49, p, 1, 1, %51, %52;\n}\n"
    : "+f"(d[0]), "+f"(d[1]), "+f"(d[2]), "+f"(d[3]), "+f"(d[4]), "+f"(d[5]), "+f"(d[6]), "+f"(d[7]), "+f"(d[8]), "+f"(d[9]), "+f"(d[10]), "+f"(d[11]), "+f"(d[12]), "+f"(d[13]), "+f"(d[14]), "+f"(d[15]), "+f"(d[16]), "+f"(d[17]), "+f"(d[18]), "+f"(d[19]), "+f"(d[20]), "+f"(d[21]), "+f"(d[22]), "+f"(d[23]), "+f"(d[24]), "+f"(d[25]), "+f"(d[26]), "+f"(d[27]), "+f"(d[28]), "+f"(d[29]), "+f"(d[30]), "+f"(d[31]), "+f"(d[32]), "+f"(d[33]), "+f"(d[34]), "+f"(d[35]), "+f"(d[36]), "+f"(d[37]), "+f"(d[38]), "+f"(d[39]), "+f"(d[40]), "+f"(d[41]), "+f"(d[42]), "+f"(d[43]), "+f"(d[44]), "+f"(d[45]), "+f"(d[46]), "+f"(d[47])
    : "l"(da), "l"(db), "r"(scaleD), "n"(TA), "n"(TB));
}

template<int TA, int TB>
__device__ __forceinline__ void wgmma_n128(float (&d)[64], uint64_t da, uint64_t db, int scaleD) {
  asm volatile("{\n.reg .pred p;\nsetp.ne.b32 p, %66, 0;\n"
    "wgmma.mma_async.sync.aligned.m64n128k16.f32.bf16.bf16 {%0, %1, %2, %3, %4, %5, %6, %7, %8, %9, %10, %11, %12, %13, %14, %15, %16, %17, %18, %19, %20, %21, %22, %23, %24, %25, %26, %27, %28, %29, %30, %31, %32, %33, %34, %35, %36, %37, %38, %39, %40, %41, %42, %43, %44, %45, %46, %47, %48, %49, %50, %51, %52, %53, %54, %55, %56, %57, %58, %59, %60, %61, %62, %63}, %64, %65, p, 1, 1, %67, %68;\n}\n"
    : "+f"(d[0]), "+f"(d[1]), "+f"(d[2]), "+f"(d[3]), "+f"(d[4]), "+f"(d[5]), "+f"(d[6]), "+f"(d[7]), "+f"(d[8]), "+f"(d[9]), "+f"(d[10]), "+f"(d[11]), "+f"(d[12]), "+f"(d[13]), "+f"(d[14]), "+f"(d[15]), "+f"(d[16]), "+f"(d[17]), "+f"(d[18]), "+f"(d[19]), "+f"(d[20]), "+f"(d[21]), "+f"(d[22]), "+f"(d[23]), "+f"(d[24]), "+f"(d[25]), "+f"(d[26]), "+f"(d[27]), "+f"(d[28]), "+f"(d[29]), "+f"(d[30]), "+f"(d[31]), "+f"(d[32]), "+f"(d[33]), "+f"(d[34]), "+f"(d[35]), "+f"(d[36]), "+f"(d[37]), "+f"(d[38]), "+f"(d[39]), "+f"(d[40]), "+f"(d[41]), "+f"(d[42]), "+f"(d[43]), "+f"(d[44]), "+f"(d[45]), "+f"(d[46]), "+f"(d[47]), "+f"(d[48]), "+f"(d[49]), "+f"(d[50]), "+f"(d[51]), "+f"(d[52]), "+f"(d[53]), "+f"(d[54]), "+f"(d[55]), "+f"(d[56]), "+f"(d[57]), "+f"(d[58]), "+f"(d[59]), "+f"(d[60]), "+f"(d[61]), "+f"(d[62]), "+f"(d[63])
    : "l"(da), "l"(db), "r"(scaleD), "n"(TA), "n"(TB));
}

template<int TA, int TB>
__device__ __forceinline__ void wgmma_n192(float (&d)[96], uint64_t da, uint64_t db, int scaleD) {
  asm volatile("{\n.reg .pred p;\nsetp.ne.b32 p, %98, 0;\n"
    "wgmma.mma_async.sync.aligned.m64n192k16.f32.bf16.bf16 {%0, %1, %2, %3, %4, %5, %6, %7, %8, %9, %10, %11, %12, %13, %14, %15, %16, %17, %18, %19, %20, %21, %22, %23, %24, %25, %26, %27, %28, %29, %30, %31, %32, %33, %34, %35, %36, %37, %38, %39, %40, %41, %42, %43, %44, %45, %46, %47, %48, %49, %50, %51, %52, %53, %54, %55, %56, %57, %58, %59, %60, %61, %62, %63, %64, %65, %66, %67, %68, %69, %70, %71, %72, %73, %74, %75, %76, %77, %78, %79, %80, %81, %82, %83, %84, %85, %86, %87, %88, %89, %90, %91, %92, %93, %94, %95}, %96, %97, p, 1, 1, %99, %100;\n}\n"
    : "+f"(d[0]), "+f"(d[1]), "+f"(d[2]), "+f"(d[3]), "+f"(d[4]), "+f"(d[5]), "+f"(d[6]), "+f"(d[7]), "+f"(d[8]), "+f"(d[9]), "+f"(d[10]), "+f"(d[11]), "+f"(d[12]), "+f"(d[13]), "+f"(d[14]), "+f"(d[15]), "+f"(d[16]), "+f"(d[17]), "+f"(d[18]), "+f"(d[19]), "+f"(d[20]), "+f"(d[21]), "+f"(d[22]), "+f"(d[23]), "+f"(d[24]), "+f"(d[25]), "+f"(d[26]), "+f"(d[27]), "+f"(d[28]), "+f"(d[29]), "+f"(d[30]), "+f"(d[31]), "+f"(d[32]), "+f"(d[33]), "+f"(d[34]), "+f"(d[35]), "+f"(d[36]), "+f"(d[37]), "+f"(d[38]), "+f"(d[39]), "+f"(d[40]), "+f"(d[41]), "+f"(d[42]), "+f"(d[43]), "+f"(d[44]), "+f"(d[45]), "+f"(d[46]), "+f"(d[47]), "+f"(d[48]), "+f"(d[49]), "+f"(d[50]), "+f"(d[51]), "+f"(d[52]), "+f"(d[53]), "+f"(d[54]), "+f"(d[55]), "+f"(d[56]), "+f"(d[57]), "+f"(d[58]), "+f"(d[59]), "+f"(d[60]), "+f"(d[61]), "+f"(d[62]), "+f"(d[63]), "+f"(d[64]), "+f"(d[65]), "+f"(d[66]), "+f"(d[67]), "+f"(d[68]), "+f"(d[69]), "+f"(d[70]), "+f"(d[71]), "+f"(d[72]), "+f"(d[73]), "+f"(d[74]), "+f"(d[75]), "+f"(d[76]), "+f"(d[77]), "+f"(d[78]), "+f"(d[79]), "+f"(d[80]), "+f"(d[81]), "+f"(d[82]), "+f"(d[83]), "+f"(d[84]), "+f"(d[85]), "+f"(d[86]), "+f"(d[87]), "+f"(d[88]), "+f"(d[89]), "+f"(d[90]), "+f"(d[91]), "+f"(d[92]), "+f"(d[93]), "+f"(d[94]), "+f"(d[95])
    : "l"(da), "l"(db), "r"(scaleD), "n"(TA), "n"(TB));
}

template <int BN, int TA, int TB>
struct WG;
template <int TA, int TB> struct WG<96, TA, TB> { static __device__ __forceinline__ void mma(float (&d)[48], uint64_t a, uint64_t b) { wgmma_n96<TA, TB>(d, a, b, 1); } };
template <int TA, int TB> struct WG<128, TA, TB> { static __device__ __forceinline__ void mma(float (&d)[64], uint64_t a, uint64_t b) { wgmma_n128<TA, TB>(d, a, b, 1); } };
template <int TA, int TB> struct WG<192, TA, TB> { static __device__ __forceinline__ void mma(float (&d)[96], uint64_t a, uint64_t b) { wgmma_n192<TA, TB>(d, a, b, 1); } };

__device__ bf16 g_h[S_LEN * D_DIM];
__device__ bf16 g_o[S_LEN * D_DIM];
__device__ bf16 g_x2[S_LEN * D_DIM];
__device__ bf16 g_u[D_DIM * F_DIM];
__device__ uint4 g_statsA[S_LEN * 8];
__device__ uint4 g_statsB[S_LEN * 8];
__device__ uint4 g_halo[256 * 512];
__device__ uint4 g_cs[8 * 1536];
__device__ __align__(128) unsigned g_sync[32];
#define g_epoch g_sync[0]
#define g_exit g_sync[1]

#define PRE_NS 400
#define POLL_NS 100
#define HALO_NS 40
#define SKEL 0
#define SUD 1000
#define GRP 0
#define U1D 0
#define VAR 1
#define RHI 232
#define RLO 40
#define HOLD 0
#define PNORM 1
#define TV 1
#define FV 1
#define PREW 1
#define EPOLL 1
#define DP2 1
#define DP3A 1
#define DP3B 1
#define DP4 1
#define CK 0
#define P1POLL 0
#define SPREAD 1
#define PROWS 32
#define PACE 1

#define TRC(wg, r, i)
#define TRG(wg, r)
#define TRE(wg, id)
#define TRA(wg, id)

__device__ __forceinline__ int logical_cta() {
  uint32_t sm, nsm;
  asm volatile("mov.u32 %0, %smid;" : "=r"(sm));
  asm volatile("mov.u32 %0, %nsmid;" : "=r"(nsm));
  if (gridDim.x == 132 && nsm == 132) {
    const int t = sm >> 1;
    if (t == 60 || t == 61) return -1;
    const int g = t < 32 ? t & 7 : t < 60 ? 1 + (t - 32) % 7 : 0;
    const int i = (t < 32 ? t >> 3 : t < 60 ? 4 + (t - 32) / 7 : t - 58) * 2 + (sm & 1);
    const int q = (0x75642310 >> (g * 4)) & 7, p = i >> 1, cp = p % 3;
    return ((q >> 1) * 4 + (cp == 2 ? 3 : p / 3)) * 8 + (q & 1) * 4 + (cp == 2 ? p / 3 : cp) * 2 + (i & 1);
  }
  const int b = blockIdx.x;
  if (b >= NCTA) return -1;
  const int g = b >> 3, i = b & 7, mq = g >> 2, jq = (mq & 1) ? 3 - (g & 3) : (g & 3);
  return ((mq * 4 + (i >> 1)) << 3) + jq * 2 + (i & 1);
}

__device__ __forceinline__ float tanh_fast(float x) {
  float y;
  asm("tanh.approx.f32 %0, %1;" : "=f"(y) : "f"(x));
  return y;
}
#define GELU_C 0.3292034911525734f
#define GELU_B 2.423681954311584f
__device__ __forceinline__ float gelu_tanh(float y, float kb) {
  return fmaf(y, tanh_fast(y * fmaf(y, y, kb)), y);
}
__device__ __forceinline__ float ex2_fast(float x) {
  float y;
  asm("ex2.approx.ftz.f32 %0, %1;" : "=f"(y) : "f"(x));
  return y;
}
__device__ __forceinline__ float rcp_fast(float x) {
  float y;
  asm("rcp.approx.ftz.f32 %0, %1;" : "=f"(y) : "f"(x));
  return y;
}
__device__ __forceinline__ uint32_t pack2(float a, float b) {
  __nv_bfloat162 v = __floats2bfloat162_rn(a, b);
  return *reinterpret_cast<uint32_t*>(&v);
}
__device__ __forceinline__ float bf_lo(uint32_t v) { return __uint_as_float(v << 16); }
__device__ __forceinline__ float bf_hi(uint32_t v) { return __uint_as_float(v & 0xffff0000u); }
__device__ __forceinline__ void unpack8(const uint4& t, float (&f)[8]) {
  f[0] = bf_lo(t.x); f[1] = bf_hi(t.x); f[2] = bf_lo(t.y); f[3] = bf_hi(t.y);
  f[4] = bf_lo(t.z); f[5] = bf_hi(t.z); f[6] = bf_lo(t.w); f[7] = bf_hi(t.w);
}
__device__ __forceinline__ uint4 pack8(const float (&f)[8]) {
  return make_uint4(pack2(f[0], f[1]), pack2(f[2], f[3]), pack2(f[4], f[5]), pack2(f[6], f[7]));
}
__device__ __forceinline__ int opaque_tid() { int v; asm volatile("mov.u32 %0, %tid.x;" : "=r"(v)); return v; }
__device__ __forceinline__ uint4 lds128(uint32_t a) {
  uint4 v;
  asm volatile("ld.shared.v4.u32 {%0,%1,%2,%3}, [%4];" : "=r"(v.x), "=r"(v.y), "=r"(v.z), "=r"(v.w) : "r"(a) : "memory");
  return v;
}
__device__ __forceinline__ float2 lds64f(uint32_t a) {
  float2 v;
  asm volatile("ld.shared.v2.f32 {%0,%1}, [%2];" : "=f"(v.x), "=f"(v.y) : "r"(a) : "memory");
  return v;
}
__device__ __forceinline__ uint32_t lds32(uint32_t a) {
  uint32_t v;
  asm volatile("ld.shared.u32 %0, [%1];" : "=r"(v) : "r"(a) : "memory");
  return v;
}
__device__ __forceinline__ void sts128(uint32_t a, const uint4& v) {
  asm volatile("st.shared.v4.u32 [%0], {%1,%2,%3,%4};" ::"r"(a), "r"(v.x), "r"(v.y), "r"(v.z), "r"(v.w) : "memory");
}
__device__ __forceinline__ void sts32(uint32_t a, uint32_t x) {
  asm volatile("st.shared.u32 [%0], %1;" ::"r"(a), "r"(x) : "memory");
}
__device__ __forceinline__ void sts64(uint32_t a, uint32_t x, uint32_t y) {
  asm volatile("st.shared.v2.u32 [%0], {%1,%2};" ::"r"(a), "r"(x), "r"(y) : "memory");
}
__device__ __forceinline__ void sts64f(uint32_t a, float x, float y) {
  asm volatile("st.shared.v2.f32 [%0], {%1,%2};" ::"r"(a), "f"(x), "f"(y) : "memory");
}
__device__ __forceinline__ void stmatrix4(uint32_t a, uint32_t r0, uint32_t r1, uint32_t r2, uint32_t r3) {
  asm volatile("stmatrix.sync.aligned.m8n8.x4.shared.b16 [%0], {%1,%2,%3,%4};" ::"r"(a), "r"(r0), "r"(r1), "r"(r2), "r"(r3) : "memory");
}
__device__ __forceinline__ void ldmatrix4(uint32_t (&r)[4], uint32_t a) {
  asm volatile("ldmatrix.sync.aligned.m8n8.x4.shared.b16 {%0,%1,%2,%3}, [%4];" : "=r"(r[0]), "=r"(r[1]), "=r"(r[2]), "=r"(r[3]) : "r"(a) : "memory");
}
__device__ __forceinline__ uint32_t movmatrix_t(uint32_t a) {
  uint32_t d;
  asm volatile("movmatrix.sync.aligned.m8n8.trans.b16 %0, %1;" : "=r"(d) : "r"(a));
  return d;
}
__device__ __forceinline__ void mma16816(float (&c)[4], uint32_t a0, uint32_t a1, uint32_t a2, uint32_t a3, uint32_t b0, uint32_t b1) {
  asm volatile("mma.sync.aligned.m16n8k16.row.col.f32.bf16.bf16.f32 {%0,%1,%2,%3}, {%4,%5,%6,%7}, {%8,%9}, {%0,%1,%2,%3};"
               : "+f"(c[0]), "+f"(c[1]), "+f"(c[2]), "+f"(c[3]) : "r"(a0), "r"(a1), "r"(a2), "r"(a3), "r"(b0), "r"(b1));
}
__device__ __forceinline__ void mma1688(float (&c)[4], uint32_t a0, uint32_t a1, uint32_t b0) {
  asm volatile("mma.sync.aligned.m16n8k8.row.col.f32.bf16.bf16.f32 {%0,%1,%2,%3}, {%4,%5}, {%6}, {%0,%1,%2,%3};"
               : "+f"(c[0]), "+f"(c[1]), "+f"(c[2]), "+f"(c[3]) : "r"(a0), "r"(a1), "r"(b0));
}
__device__ __forceinline__ uint4 ld_volatile4(const uint4* p) {
  uint4 v;
  asm volatile("ld.relaxed.gpu.global.v4.u32 {%0,%1,%2,%3}, [%4];" : "=r"(v.x), "=r"(v.y), "=r"(v.z), "=r"(v.w) : "l"(p) : "memory");
  return v;
}
__device__ __forceinline__ void red_release(unsigned* p) {
  asm volatile("fence.proxy.async;\nred.relaxed.gpu.global.add.u32 [%0], 1;" ::"l"(p) : "memory");
}
__device__ __forceinline__ void tma_store(const CUtensorMap* tm, uint32_t src, int c0, int c1, int c2, int c3) {
  asm volatile("cp.async.bulk.tensor.4d.global.shared::cta.bulk_group [%0, {%2, %3, %4, %5}], [%1];" ::"l"((uint64_t)tm), "r"(src),
               "r"(c0), "r"(c1), "r"(c2), "r"(c3) : "memory");
}
__device__ __forceinline__ void bulk_commit() { asm volatile("cp.async.bulk.commit_group;" ::: "memory"); }
template <int N>
__device__ __forceinline__ void bulk_wait() { asm volatile("cp.async.bulk.wait_group %0;" ::"n"(N) : "memory"); }
template <int N>
__device__ __forceinline__ void bulk_wait_read() { asm volatile("cp.async.bulk.wait_group.read %0;" ::"n"(N) : "memory"); }
__device__ __forceinline__ void fence_proxy_async_smem() { asm volatile("fence.proxy.async.shared::cta;" ::: "memory"); }
__device__ __forceinline__ void spin_until(const unsigned* p, unsigned target) {
  asm volatile(
      "{\n.reg .pred p;\n.reg .u32 v, c;\nmov.u32 c, 0;\n"
      "SPIN_LOOP:\n"
      "ld.relaxed.gpu.global.u32 v, [%0];\n"
      "sub.u32 v, v, %1;\n"
      "setp.ge.s32 p, v, 0;\n"
      "@p bra.uni SPIN_DONE;\n"
      "add.u32 c, c, 1;\n"
      "setp.lt.u32 p, c, 4194304;\n"
      "@p bra.uni SPIN_LOOP;\n"
      "trap;\n"
      "SPIN_DONE:\n"
      "fence.acquire.gpu;\n}\n" ::"l"(p), "r"(target) : "memory");
}
__device__ __forceinline__ void e_expect_tx(uint32_t bar, uint32_t bytes) {
  asm volatile("{\n.reg .pred p;\nelect.sync _|p, 0xffffffff;\n@p mbarrier.arrive.expect_tx.shared::cta.b64 _, [%0], %1;\n}\n" ::"r"(bar), "r"(bytes) : "memory");
}
__device__ __forceinline__ void e_tma_load(uint32_t dst, const CUtensorMap* tm, uint32_t bar, int c0, int c1, int c2, int c3) {
  asm volatile(
      "{\n.reg .pred p;\nelect.sync _|p, 0xffffffff;\n"
      "@p cp.async.bulk.tensor.4d.shared::cluster.global.mbarrier::complete_tx::bytes [%0], [%1, {%3, %4, %5, %6}], [%2];\n}\n" ::"r"(dst),
      "l"((uint64_t)tm), "r"(bar), "r"(c0), "r"(c1), "r"(c2), "r"(c3) : "memory");
}

__device__ __forceinline__ void e_arrive(uint32_t bar) {
  asm volatile("{\n.reg .pred p;\nelect.sync _|p, 0xffffffff;\n@p mbarrier.arrive.shared::cta.b64 _, [%0];\n}\n" ::"r"(bar) : "memory");
}
__device__ __forceinline__ void e_tma_store(const CUtensorMap* tm, uint32_t src, int c0, int c1, int c2, int c3) {
  asm volatile("{\n.reg .pred p;\nelect.sync _|p, 0xffffffff;\n"
               "@p cp.async.bulk.tensor.4d.global.shared::cta.bulk_group [%0, {%2, %3, %4, %5}], [%1];\n}\n" ::"l"((uint64_t)tm), "r"(src),
               "r"(c0), "r"(c1), "r"(c2), "r"(c3) : "memory");
}
__device__ __forceinline__ void e_red_release(unsigned* p) {
  asm volatile("{\n.reg .pred p;\nfence.proxy.async;\nelect.sync _|p, 0xffffffff;\n@p red.relaxed.gpu.global.add.u32 [%0], 1;\n}\n" ::"l"(p) : "memory");
}
__device__ __forceinline__ void e_tma_prefetch(const CUtensorMap* tm, int c0, int c1, int c2) {
  asm volatile(
      "{\n.reg .pred p;\nelect.sync _|p, 0xffffffff;\n"
      "@p cp.async.bulk.prefetch.tensor.4d.L2.global [%0, {%1, %2, %3, %4}];\n}\n" ::"l"((uint64_t)tm), "r"(c0), "r"(c1), "r"(c2), "r"(0) : "memory");
}

#define RING_U 24
#define OFF_STG (RING_U * 8192)
#define OFF_BAR (OFF_STG + 32768)
#define OFF_FULL (OFF_BAR)
#define OFF_EMPTY (OFF_BAR + 192)
#define OFF_STR (OFF_BAR + 256)
#define OFF_OST (OFF_BAR + 272)
#define OFF_TR (OFF_BAR + 288)
#define OFF_TU0 (OFF_BAR + 304)
#define OFF_TU1 (OFF_BAR + 320)
#define OFF_SFR (OFF_BAR + 336)
#define OFF_K01 (OFF_BAR + 352)
#define OFF_RES (OFF_BAR + 368)
#define OFF_DEP (OFF_B2 + 256)
#define OFF_CS (OFF_BAR + 384)
#define OFF_ST (OFF_CS + 768)
#define OFF_B1 (OFF_ST + 576)
#define OFF_B2 (OFF_B1 + 896)
#define SMEM_TOTAL (OFF_B2 + 256 + 80)

enum { K_G1 = 0, K_RES = 2, K_G2 = 4, K_G3 = 6, K_G3S = 8, K_G4 = 9, K_G4S = 11 };
enum { E_O = 1, E_H = 3, E_UA = 5, E_UB = 6, E_U1 = 7, E_X = 8 };
#define MAXSEG 80
#define MAXRUN 56

struct Params {
  CUtensorMap xq[2], xr[2], wqkv, o_k, wo, h_m, w1a, w1b, w1h, w2s, w2d, u_k, o_s, out_s[2], u_s, u_h;
  uint2 seg[MAXSEG];
  uint32_t run[2][MAXRUN];
  int nseg;
  uint32_t pre, poll, u0d, u1d, sud, map, od[2];
};

#define LCTA __shfl_sync(0xffffffffu, (int)lds32(sbase + OFF_K01 + 8), 0)
#define opaque_cta() LCTA

template <int WHICH>
__device__ __forceinline__ void producer(const Params& P, uint32_t sbase) {
  const int cta = LCTA, m = cta >> 3, j = cta & 7;
  uint32_t tail8 = 0;
  const int nseg = P.nseg;
#pragma unroll 1
  for (int si = 0; si < nseg; si++) {
    const uint32_t sg = P.seg[si].x;
    const int kind = sg & 15, n = (sg >> 10) & 63, ks = (((sg >> 16) & 1) + 1) * 64, dep = (sg >> 17) & 31, l = (sg >> 27) & 1;
    const bool own = (sg >> 29) & 1;
    const int mk = m * (kind >= K_G4 ? 128 : 64);
    int kk = ((sg >> 4) & 63) * 64, skip = -1;
    if (own) kk += mk;
    if ((sg >> 30) & 1) {
      skip = mk + (kind >= K_G4 ? kk & 64 : (sg >> 31) * 1024);
      if (kk >= skip) kk += ks;
    }
    const int w = (kind < K_G3S ? kind : kind - 1) & 1;
    const int set = (kind == K_G3S || kind == K_G4S) ? 2 : w;
    const CUtensorMap* mp;
    int c0 = kk, c1 = kk, c3 = 0, d0 = 0, d1 = ks, size, soff, nx = 0;
    uint32_t bytes;
    if (kind < K_RES) {
      size = 6;
      if (WHICH == 0) { mp = &P.wqkv; c0 = m * 64; soff = 16384; bytes = 24576; }
      else { mp = &P.xq[l]; c1 = 0; c3 = w * 16 + j * 2; d0 = ks; d1 = 0; soff = 0; bytes = 16384; }
    } else if (kind < K_G3) {
      size = 3;
      if (WHICH == 0) { mp = &P.wo; c0 = j * 128; soff = 0; bytes = 16384; }
      else { mp = &P.o_k; c1 = (w * 16 + m) * 64; d0 = ks; d1 = 0; soff = 16384; bytes = 8192; }
    } else if (kind < K_G4) {
      size = kind == K_G3S ? 6 : 4;
      if (WHICH == 0) {
        soff = 16384;
        if (kind == K_G3 + 1) { mp = &P.w1b; c0 = 2048 + m * 96 + (m & 1) * 32; nx = 1; bytes = 16384; }
        else { mp = &P.w1a; c0 = m * 128; nx = kind == K_G3S ? 2 : 0; bytes = kind == K_G3S ? 32768 : 16384; }
      } else { mp = &P.h_m; c0 = j * 128; soff = 0; bytes = 16384; }
    } else {
      size = kind == K_G4S ? 4 : 3;
      if (WHICH == 0) {
        soff = 16384;
        if (kind == K_G4S) { mp = &P.w2d; c0 = m * 64; bytes = 16384; }
        else { mp = &P.w2s; c0 = (w * 16 + m) * 64; bytes = 8192; }
      } else { mp = &P.u_k; c1 = j * 128; d0 = ks; d1 = 0; soff = 0; bytes = 16384; }
    }
    if (WHICH == 1 && own) bytes = 0;
    uint32_t wc = P.seg[si].y;
    const uint32_t fb0 = sbase + OFF_FULL + set * 64, dst0 = sbase + soff, step = size * 8192;
    uint32_t fb = fb0 + (wc >> 29) * 8, dst = dst0 + ((sg >> 22) & 31) * 8192;
    wc = (wc & 0x0fffffffu) | 0x50000000u;
    if (WHICH == 1 && !SKEL && dep) {
      mbar_wait(sbase + OFF_DEP + (dep & 15) * 8, dep >> 4);
      asm volatile("fence.proxy.async.global;" ::: "memory");
    }
#pragma unroll 1
    for (int i = n; i > 0; i--) {
#pragma unroll 1
      for (uint32_t q = wc & 3; q; q--) {
        mbar_wait(sbase + OFF_EMPTY + (tail8 & 0x38), (tail8 >> 6) & 1);
        tail8 += 8;
      }
      if (WHICH == 0 || !own) e_tma_load(dst, mp, fb, c0, c1, 0, c3);
      if (WHICH == 0 && nx) {
        if (nx == 2) e_tma_load(dst + 16384, &P.w1b, fb, 2048 + m * 96 + (m & 1) * 32, c1, 0, 0);
        e_tma_load(dst + nx * 16384 - 8192, &P.w1h, fb, 0, c1, 64 + m * 3 + 2 - (m & 1) * 2, 0);
      }
      e_expect_tx(fb, bytes);
      wc = (wc >> 2) | 0x40000000u;
      c0 += d0; c1 += d1;
      kk += ks;
      if (kk == skip) { c0 += d0; c1 += d1; }
      fb = fb == fb0 + 56 ? fb0 : fb + 8;
      dst += step;
      if (dst == dst0 + RING_U * 8192) dst = dst0;
    }
  }
}

struct Cons {
  uint32_t nsolo, nshr;
  int ri;
  uint32_t prev;
};
template <int MW, int BN, int TA, int TB, int SZ0, int SZ1, int AOFF, int BOFF, int ASH, int BSH, int DP>
__device__ __forceinline__ void gemm_runs(const Params& P, uint32_t sbase, Cons& c, float (&acc)[MW][BN / 2], int wg) {
  uint32_t prev = 0, prev2 = 0;
  uint32_t r;
#pragma unroll
  for (int b = 0; b < MW; b++)
#pragma unroll
    for (int i = 0; i < BN / 2; i++) asm volatile("" : "+f"(acc[b][i])::"memory");
  const bool lead = (threadIdx.x & 127) == 0;
  if (DP == 2) { wgmma_fence(); wgmma_commit(); wgmma_commit(); }
#pragma unroll 1
  do {
    r = P.run[wg][c.ri];
    const int sh = (r >> 14) & 1, pre = (r >> 15) & 15, post = (r >> 19) & 15;
    uint32_t so = ((r >> 6) & 31) * 512, e8 = (r >> 8) & 0x38;
    const uint32_t size = (sh ? SZ1 : SZ0) * 512;
    uint32_t cnt = sh ? c.nshr : c.nsolo;
    const uint32_t fb0 = sbase + OFF_FULL + (sh ? 2 : wg) * 64, eb0 = sbase + OFF_EMPTY + 2 - sh;
    const uint32_t own = TA && TB ? (r >> 25) & 3 : 0, oo = own ? OFF_STG - 16384 + own * 16384 - so * 16 : 0;
    const uint64_t da0 = make_desc(sbase + AOFF + (sh ? ASH * wg : 0) + (TB ? oo : 0), TA ? 8192 : 16, 1024);
    const uint64_t db0 = make_desc(sbase + BOFF + (sh ? BSH * wg : 0) + (TB ? 0 : oo), TB ? 8192 : 16, 1024);
    TRC(wg, c.ri, 0);
    if (pre) bar_sync(pre, 256);
    if (own) mbar_wait(sbase + (TB ? OFF_TR - 8 + own * 8 : OFF_TU0 - 16 + own * 16), (r >> 27) & 1);
    int i = r & 63;
#pragma unroll 1
    do {
      mbar_wait(fb0 + (cnt & 7) * 8, (cnt >> 3) & 1);
      wgmma_fence();
#pragma unroll
      for (int k = 0; k < 4; k++) {
#pragma unroll
        for (int b = 0; b < MW; b++)
          WG<BN, TA, TB>::mma(acc[b], da0 + so + b * 512 + (TA ? k * 128 : k * 2), db0 + so + (TB ? k * 128 : k * 2));
        if (k == (DP == 3 ? CK : 3)) wgmma_commit();
      }
      if (post && i == 1) bar_arrive(post, 256);
      cnt++;
      so += size;
      if (so == RING_U * 512) so = 0;
      wgmma_wait<DP == 2 ? 2 : 1>();
      const uint32_t rel = DP >= 2 ? prev2 : prev;
      if (rel && lead) mbar_arrive_n(rel & ~7u, rel & 7);
      prev2 = prev;
      prev = eb0 + e8;
      e8 = (e8 + 8) & 0x38;
    } while (--i);
    if (sh) c.nshr = cnt; else c.nsolo = cnt;
    if (r & (1u << 23)) {
      if (DP == 3) wgmma_commit();
      wgmma_wait<0>();
      if (DP >= 2 && prev2 && lead) mbar_arrive_n(prev2 & ~7u, prev2 & 7);
      if (lead) mbar_arrive_n(prev & ~7u, prev & 7);
      prev = prev2 = 0;
    }
    TRC(wg, c.ri, 3);
    c.ri++;
  } while (!(r & (1u << 24)));
  if (BN == 192) { c.prev = prev & ~7u; return; }
  if (DP == 3) wgmma_commit();
  wgmma_wait<0>();
#pragma unroll
  for (int b = 0; b < MW; b++)
#pragma unroll
    for (int i = 0; i < BN / 2; i++) asm volatile("" : "+f"(acc[b][i])::"memory");
}

__device__ __forceinline__ void stage_tile128(const uint32_t (&pk)[32], uint32_t wbase, int lane) {
  const int r7 = lane & 7;
  const uint32_t sa = wbase + (((lane >> 3) & 1) * 8 + r7) * 128;
#pragma unroll
  for (int j = 0; j < 8; j++)
    stmatrix4(sa + (j >> 2) * 8192 + ((((j * 2 + (lane >> 4)) & 7) ^ r7) << 4), pk[j * 4 + 0], pk[j * 4 + 1], pk[j * 4 + 2], pk[j * 4 + 3]);
}
__device__ __forceinline__ void tile_stats(const float (&acc)[64], uint4* dst, unsigned tag, int t, float z = 0.f) {
  float s0 = z, s1 = z, s2 = z, s3 = z, q0 = z, q1 = z, q2 = z, q3 = z;
#pragma unroll
  for (int j = 0; j < 16; j++) {
    s0 += acc[j * 4 + 0]; s2 += acc[j * 4 + 1]; s1 += acc[j * 4 + 2]; s3 += acc[j * 4 + 3];
    q0 = fmaf(acc[j * 4 + 0], acc[j * 4 + 0], q0); q2 = fmaf(acc[j * 4 + 1], acc[j * 4 + 1], q2);
    q1 = fmaf(acc[j * 4 + 2], acc[j * 4 + 2], q1); q3 = fmaf(acc[j * 4 + 3], acc[j * 4 + 3], q3);
  }
  s0 += s2; s1 += s3; q0 += q2; q1 += q3;
  float s = (t & 1) ? s1 : s0, q = (t & 1) ? q1 : q0;
  s += __shfl_xor_sync(0xffffffffu, (t & 1) ? s0 : s1, 1); q += __shfl_xor_sync(0xffffffffu, (t & 1) ? q0 : q1, 1);
  s += __shfl_xor_sync(0xffffffffu, s, 2); q += __shfl_xor_sync(0xffffffffu, q, 2);
  if (t < 2) __stcg(dst + t * 8, make_uint4(__float_as_uint(s), tag, __float_as_uint(q), tag));
}
__device__ __forceinline__ void store_rows(const CUtensorMap* mp, uint32_t src, int col, int row, uint32_t bar, int lane) {
  fence_proxy_async_smem();
  __syncwarp();
  if (lane == 0) {
    tma_store(mp, src, col, row, 0, 0);
    tma_store(mp, src + 8192, col + 64, row, 0, 0);
    bulk_commit();
    bulk_wait<0>();
    mbar_arrive(bar);
  }
  __syncwarp();
}

__device__ __forceinline__ void attention(const Params& P, float (&acc)[2][96], uint32_t sbase, Cons& c, int wg, int l, unsigned tag) {
  const uint32_t r = P.run[wg][c.ri];
  const uint32_t slot0 = sbase + OFF_STG + wg * 16384;
  TRC(wg, c.ri, 0);
        if (PREW) {
          const int cta = opaque_cta(), tid = opaque_tid();
          if (tid & 32) {
            uint4* hp = &g_halo[((wg * 8 + (cta & 7)) * 16 + (cta >> 3)) * 512 + ((tid >> 6) & 1) * 256 + (tid & 31)];
#pragma unroll
            for (int i = 0; i < 8; i++) __stcg(hp + i * 32, make_uint4(0, 0, 0, 0));
          }
        }
  const uint64_t da0 = make_desc(sbase, 16, 1024), db0 = make_desc(sbase + 16384, 8192, 1024);
  const uint32_t so0 = ((r >> 6) & 31) * 512, so1 = so0 == (RING_U - 6) * 512 ? 0 : so0 + 6 * 512, so2 = so1 == (RING_U - 6) * 512 ? 0 : so1 + 6 * 512;
  {
    uint32_t so = so0;
#pragma unroll 1
    for (int i = 0; i < 3; i++) {
      mbar_wait(sbase + OFF_FULL + wg * 64 + (c.nsolo & 7) * 8, (c.nsolo >> 3) & 1);
      if (i == 0) TRC(wg, c.ri, 2);
      c.nsolo++;
      wgmma_fence();
#pragma unroll
      for (int k = 0; k < 4; k++) WG<192, 0, 1>::mma(acc[1], da0 + so + 512 + k * 2, db0 + so + k * 128);
      wgmma_commit();
      wgmma_wait<1>();
      if (i == 0 && (threadIdx.x & 127) == 0) mbar_arrive_n(c.prev, 2);
      so = so == (RING_U - 6) * 512 ? 0 : so + 6 * 512;
    }
  }
#define TAIL(so)                                                                                                           \
  _Pragma("unroll") for (int k = 0; k < 4; k++) WG<192, 0, 1>::mma(acc[0], da0 + (so) + k * 2, db0 + (so) + k * 128);      \
  wgmma_commit()
#define EB(i) (sbase + OFF_EMPTY + (((r >> 11) + (i)) & 7) * 8)
#define PIN(b, i0, i1) _Pragma("unroll") for (int i = i0; i < i1; i++) asm volatile("" : "+f"(acc[b][i])::"memory")
#define PK(b, jj, h) pack2(acc[b][(jj) * 4 + (h) * 2], acc[b][(jj) * 4 + (h) * 2 + 1])
  mbar_wait(sbase + OFF_STR + wg * 8, l);
  {
    const uint64_t de = (uint64_t)((slot0 & 0x3FFFF) >> 4) | ((uint64_t)8 << 32);
    wgmma_fence();
    wgmma_n192<0, 0>(acc[1], de + 64, de + 128, 1);
    wgmma_commit();
    wgmma_n192<0, 0>(acc[0], de, de + 128, 1);
  }
  TAIL(so0);
  TAIL(so1);
  const int cta = opaque_cta(), tid = opaque_tid(), lane = tid & 31, g = lane >> 2, t = lane & 3;
  const int wq = __shfl_sync(0xffffffffu, (tid >> 5) & 3, 0), hf = wq & 1;
  const int T = wg * 8 + (cta & 7), tn = cta >> 3;
  uint4* const hp = &g_halo[(T * 16 + tn) * 512 + (wq >> 1) * 256 + lane];
  uint32_t Q[2][8][2], K[2][8][2], V[2][8][2];
#define PACKKV(b)                                                                                       \
  _Pragma("unroll") for (int jj = 7; jj >= 0; jj--) {                                                   \
    V[b][jj][1] = movmatrix_t(PK(b, jj + 16, 1)); V[b][jj][0] = PK(b, jj + 16, 0);                      \
  }                                                                                                     \
  _Pragma("unroll") for (int jj = 7; jj >= 0; jj--) { K[b][jj][1] = PK(b, jj + 8, 1); K[b][jj][0] = PK(b, jj + 8, 0); }
#define PACKQ(b)                                                                                        \
  _Pragma("unroll") for (int jj = 7; jj >= 0; jj--) {                                                   \
    V[b][jj][0] = movmatrix_t(V[b][jj][0]); Q[b][jj][1] = PK(b, jj, 1); Q[b][jj][0] = PK(b, jj, 0);     \
  }
#define HALO_OUT(b, a)                                                                                  \
  sts128(a, make_uint4(K[b][0][1], K[b][1][1], K[b][2][1], K[b][3][1]));                                \
  sts128(a + 512, make_uint4(K[b][4][1], K[b][5][1], K[b][6][1], K[b][7][1]));                          \
  sts128(a + 1024, make_uint4(V[b][0][1], V[b][1][1], V[b][2][1], V[b][3][1]));                         \
  sts128(a + 1536, make_uint4(V[b][4][1], V[b][5][1], V[b][6][1], V[b][7][1]))
  wgmma_wait<TV ? 2 : 3>();
  PIN(1, 0, 96);
  TRE(wg, l * 32 + 1);
  PACKKV(1);
  if (!hf) { HALO_OUT(1, slot0 + (5 + wq) * 2048 + lane * 16); }
  else if (T < 15) {
#pragma unroll
    for (int i = 0; i < 4; i++) {
      __stcg(hp + i * 32, make_uint4(K[1][i * 2][1], tag, K[1][i * 2 + 1][1], tag));
      __stcg(hp + (i + 4) * 32, make_uint4(V[1][i * 2][1], tag, V[1][i * 2 + 1][1], tag));
    }
  }
  TRE(wg, l * 32 + 2);
  wgmma_fence();
  TAIL(so2);
  wgmma_wait<2>();
  if ((tid & 127) == 0) mbar_arrive_n(EB(0), 2);
  PACKQ(1);
  wgmma_wait<1>();
  if ((r >> 19) & 15) bar_arrive((r >> 19) & 15, 256);
  if ((tid & 127) == 0) mbar_arrive_n(EB(1), 2);
  const bool o0 = 2 * t > g, o1 = 2 * t + 1 > g;
  float rk[2][4], rq[2][4];
#pragma unroll
  for (int b = 0; b < 2; b++) {
    const uint32_t a = sbase + OFF_ST + ((wq >> 1) * 72 + 8 + b * 32 + hf * 16) * 4;
    const float kscale = 0.17677669529663687f * 1.4426950408889634f;
    const float q0 = __uint_as_float(lds32(a + g * 4)) * kscale, q1 = __uint_as_float(lds32(a + g * 4 + 32)) * kscale;
    const uint32_t a0 = a + t * 8 - (o0 ? 32 : 0), a1 = a + t * 8 + 4 - (o1 ? 32 : 0);
    rk[b][0] = __uint_as_float(lds32(a0)); rk[b][1] = __uint_as_float(lds32(a1));
    rk[b][2] = __uint_as_float(lds32(a0 + 32)); rk[b][3] = __uint_as_float(lds32(a1 + 32));
    rq[b][0] = rk[b][0] * q0; rq[b][1] = rk[b][1] * q0; rq[b][2] = rk[b][2] * q1; rq[b][3] = rk[b][3] * q1;
  }
  const bool remote = !hf && T > 0 && !SKEL;
  uint4 hv[8];
#pragma unroll
  for (int i = 0; i < 8; i++)
    asm volatile("{\n.reg .pred p;\nsetp.ne.u32 p, %5, 0;\nmov.u32 %0, 0;\nmov.u32 %1, 0;\nmov.u32 %2, 0;\nmov.u32 %3, 0;\n"
                 "@p ld.relaxed.gpu.global.v4.u32 {%0,%1,%2,%3}, [%4];\n}\n"
                 : "=&r"(hv[i].x), "=&r"(hv[i].y), "=&r"(hv[i].z), "=&r"(hv[i].w) : "l"(hp - 16 * 512 + i * 32), "r"((int)remote) : "memory");
  wgmma_wait<0>();
  PIN(0, 0, 96);
  if ((tid & 127) == 0) mbar_arrive_n(EB(2), 2);
  TRC(wg, c.ri, 3);
  c.ri++;
  PACKKV(0);
  HALO_OUT(0, slot0 + (hf ? 3 + wq : 1 + wq) * 2048 + lane * 16);
  PACKQ(0);
  TRE(wg, l * 32 + 29);
  bar_sync(7 + wg, 128);
  uint32_t HK[2][8], HV[2][8];
#pragma unroll
  for (int b = 1; b >= 0; b--) {
    if (b == 1 || hf) {
      const uint32_t a = slot0 + (b * 4 + wq) * 2048 + lane * 16;
      const uint4 k0 = lds128(a), k1 = lds128(a + 512), v0 = lds128(a + 1024), v1 = lds128(a + 1536);
      HK[b][0] = k0.x; HK[b][1] = k0.y; HK[b][2] = k0.z; HK[b][3] = k0.w; HK[b][4] = k1.x; HK[b][5] = k1.y; HK[b][6] = k1.z; HK[b][7] = k1.w;
      HV[b][0] = v0.x; HV[b][1] = v0.y; HV[b][2] = v0.z; HV[b][3] = v0.w; HV[b][4] = v1.x; HV[b][5] = v1.y; HV[b][6] = v1.z; HV[b][7] = v1.w;
    } else {
      if (remote) {
#pragma unroll 1
        for (int it = 0; it < (1 << 20); it++) {
          bool ok = true;
#pragma unroll
          for (int i = 0; i < 8; i++) ok = ok && hv[i].y == tag && hv[i].w == tag;
          if (__all_sync(0xffffffffu, ok)) break;
          __nanosleep(HALO_NS);
#pragma unroll
          for (int i = 0; i < 8; i++) hv[i] = ld_volatile4(hp - 16 * 512 + i * 32);
        }
      }
#pragma unroll
      for (int i = 0; i < 4; i++) { HK[0][i * 2] = hv[i].x; HK[0][i * 2 + 1] = hv[i].z; HV[0][i * 2] = hv[i + 4].x; HV[0][i * 2 + 1] = hv[i + 4].z; }
    }
  }
  TRE(wg, l * 32 + 3);
  float S[2][2][3][4];
#pragma unroll
  for (int b = 1; b >= 0; b--)
#pragma unroll
    for (int u = 0; u < 2; u++)
#pragma unroll
      for (int kt = 0; kt < 3; kt++) S[b][u][kt][0] = S[b][u][kt][1] = S[b][u][kt][2] = S[b][u][kt][3] = 0.f;
#pragma unroll
  for (int ks = 0; ks < 2; ks++)
#pragma unroll
    for (int b = 1; b >= 0; b--)
#pragma unroll
      for (int u = 0; u < 2; u++) {
        const int j0 = u * 4 + ks * 2;
        mma16816(S[b][u][1], Q[b][j0][0], Q[b][j0][1], Q[b][j0 + 1][0], Q[b][j0 + 1][1], K[b][j0][0], K[b][j0 + 1][0]);
        mma16816(S[b][u][2], Q[b][j0][0], Q[b][j0][1], Q[b][j0 + 1][0], Q[b][j0 + 1][1], K[b][j0][1], K[b][j0 + 1][1]);
        mma16816(S[b][u][0], Q[b][j0][0], Q[b][j0][1], Q[b][j0 + 1][0], Q[b][j0 + 1][1], HK[b][j0], HK[b][j0 + 1]);
      }
  TRE(wg, l * 32 + 4);
  const uint32_t mold = (o0 ? 0xffffu : 0u) | (o1 ? 0xffff0000u : 0u);
  const float NEG = -3.0e38f;
  const bool first = T == 0 && !hf;
  uint32_t pl[2][2], ph[2][2];
#pragma unroll
  for (int b = 1; b >= 0; b--)
#pragma unroll
    for (int u = 0; u < 2; u++) {
      float a0 = (o0 ? S[b][u][0][0] : S[b][u][1][0]) * rq[b][0], a1 = (o1 ? S[b][u][0][1] : S[b][u][1][1]) * rq[b][1];
      float b0 = (o0 ? S[b][u][1][2] : S[b][u][2][2]) * rq[b][2], b1 = (o1 ? S[b][u][1][3] : S[b][u][2][3]) * rq[b][3];
      if (b == 0) { a0 = (first && o0) ? NEG : a0; a1 = (first && o1) ? NEG : a1; }
      float m0 = fmaxf(a0, a1), m1 = fmaxf(b0, b1);
      m0 = fmaxf(m0, __shfl_xor_sync(0xffffffffu, m0, 1)); m1 = fmaxf(m1, __shfl_xor_sync(0xffffffffu, m1, 1));
      m0 = fmaxf(m0, __shfl_xor_sync(0xffffffffu, m0, 2)); m1 = fmaxf(m1, __shfl_xor_sync(0xffffffffu, m1, 2));
      a0 = ex2_fast(a0 - m0); a1 = ex2_fast(a1 - m0); b0 = ex2_fast(b0 - m1); b1 = ex2_fast(b1 - m1);
      float s0 = a0 + a1, s1 = b0 + b1;
      s0 += __shfl_xor_sync(0xffffffffu, s0, 1); s1 += __shfl_xor_sync(0xffffffffu, s1, 1);
      s0 += __shfl_xor_sync(0xffffffffu, s0, 2); s1 += __shfl_xor_sync(0xffffffffu, s1, 2);
      s0 = rcp_fast(s0); s1 = rcp_fast(s1);
      pl[b][u] = pack2(a0 * rk[b][0] * s0, a1 * rk[b][1] * s0); ph[b][u] = pack2(b0 * rk[b][2] * s1, b1 * rk[b][3] * s1);
    }
  float O[2][2][4][4];
#pragma unroll
  for (int b = 1; b >= 0; b--)
#pragma unroll
    for (int u = 0; u < 2; u++)
#pragma unroll
      for (int nt = 0; nt < 4; nt++) {
        O[b][u][nt][0] = O[b][u][nt][1] = O[b][u][nt][2] = O[b][u][nt][3] = 0.f;
        mma1688(O[b][u][nt], pl[b][u] & ~mold, ph[b][u] & mold, V[b][u * 4 + nt][0]);
      }
#pragma unroll
  for (int b = 1; b >= 0; b--)
#pragma unroll
    for (int u = 0; u < 2; u++)
#pragma unroll
      for (int nt = 0; nt < 4; nt++) mma1688(O[b][u][nt], 0u, ph[b][u] & ~mold, V[b][u * 4 + nt][1]);
#pragma unroll
  for (int b = 1; b >= 0; b--)
#pragma unroll
    for (int u = 0; u < 2; u++)
#pragma unroll
      for (int nt = 0; nt < 4; nt++) mma1688(O[b][u][nt], pl[b][u] & mold, 0u, HV[b][u * 4 + nt]);
  {
    uint32_t dep = 0;
#pragma unroll
    for (int i = 0; i < 16; i++) dep |= __float_as_uint(O[i >> 3][(i >> 2) & 1][i & 3][0]);
    bar_arrive(3 + wg + (dep & lds32(sbase + OFF_K01 + 4)), 256);
  }
  TRE(wg, l * 32 + 5);
  const float one = __uint_as_float(lds32(sbase + OFF_K01 + 12));
  const int r7 = lane & 7;
#pragma unroll
  for (int b = 1; b >= 0; b--) {
    const uint32_t rb = slot0 + (b * 4 + wq) * 2048 + (((lane >> 3) & 1) * 8 + r7) * 128;
#pragma unroll
    for (int u = 0; u < 2; u++) {
      const float c0 = 1.f, c1 = 1.f;
#pragma unroll
      for (int np = 0; np < 2; np++)
        stmatrix4(rb + (((u * 4 + np * 2 + (lane >> 4)) ^ r7) << 4), pack2(O[b][u][2 * np][0] * c0, O[b][u][2 * np][1] * c0),
                  pack2(O[b][u][2 * np][2] * c1, O[b][u][2 * np][3] * c1), pack2(O[b][u][2 * np + 1][0] * c0, O[b][u][2 * np + 1][1] * c0),
                  pack2(O[b][u][2 * np + 1][2] * c1, O[b][u][2 * np + 1][3] * c1));
    }
  }
  fence_proxy_async_smem();
  __syncwarp();
  if (lane == 0) mbar_arrive(sbase + OFF_OST + wg * 8);
  TRE(wg, l * 32 + 6);
}

__device__ __forceinline__ uint4 ext_row(float mean) {
  const uint32_t hi = pack2(mean, mean);
  return make_uint4(hi, pack2(mean - bf_lo(hi), 0.f), 0, 0);
}
__device__ __forceinline__ uint4 ext_col(float cs) {
  cs *= -0.5f;
  const float hi = bf_lo(pack2(cs, 0.f));
  return make_uint4(pack2(hi, cs - hi), pack2(hi, 0.f), 0, 0);
}

__device__ __forceinline__ void init_down(float (&acc)[1][64], const uint32_t (&xr)[32], uint32_t sbase) {
  const int tid = opaque_tid();
  uint16_t bb0, bb1;
  const uint32_t ba = sbase + OFF_B2 + ((tid >> 5) * 16 + ((tid & 31) >> 2)) * 2;
  asm volatile("ld.shared.u16 %0, [%1];" : "=h"(bb0) : "r"(ba) : "memory");
  asm volatile("ld.shared.u16 %0, [%1];" : "=h"(bb1) : "r"(ba + 16) : "memory");
  const float k = 2.f * GELU_C, bias0 = __uint_as_float((uint32_t)bb0 << 16) * k, bias1 = __uint_as_float((uint32_t)bb1 << 16) * k;
#pragma unroll
  for (int j = 0; j < 16; j++) {
    acc[0][j * 4 + 0] = fmaf(bf_lo(xr[j * 2]), k, bias0); acc[0][j * 4 + 1] = fmaf(bf_hi(xr[j * 2]), k, bias0);
    acc[0][j * 4 + 2] = fmaf(bf_lo(xr[j * 2 + 1]), k, bias1); acc[0][j * 4 + 3] = fmaf(bf_hi(xr[j * 2 + 1]), k, bias1);
  }
}
template <int BN>
__device__ __forceinline__ void mixer_up(const Params& P, uint32_t sbase, Cons& c, int wg, int l, float (&acc4)[1][64], const uint32_t (&xr)[32]) {
  float acc[2][BN / 2];
  {
    const uint32_t ba = sbase + OFF_B1 + (BN == 96 ? 512 : 0) + (opaque_tid() & 3) * 8;
#pragma unroll
    for (int j = 0; j < BN / 8; j++) {
      const float2 bv = lds64f(ba + j * 32);
#pragma unroll
      for (int b = 0; b < 2; b++) { acc[b][j * 4 + 0] = acc[b][j * 4 + 2] = bv.x; acc[b][j * 4 + 1] = acc[b][j * 4 + 3] = bv.y; }
    }
  }
  gemm_runs<2, BN, 1, 1, 4, 6, 0, 16384, 0, 16384, 1>(P, sbase, c, acc, wg);
  TRE(wg, l * 32 + 16);
  if (BN == 96) init_down(acc4, xr, sbase);
  const int tid = opaque_tid(), lane = tid & 31, r7 = lane & 7;
  const uint32_t a0 = sbase + OFF_STG + (((tid >> 5) & 3) * 16 + ((lane >> 3) & 1) * 8 + r7) * 128;
  uint32_t sw[4];
#pragma unroll
  for (int k = 0; k < 4; k++) sw[k] = a0 + (((k * 2 + (lane >> 4)) ^ r7) << 4);
  float k01 = GELU_B, knext = GELU_B;
  const uint32_t r = P.run[wg][c.ri];
  uint32_t so = ((r >> 6) & 31) * 512, e8 = (r >> 8) & 0x38;
  const uint64_t da0 = make_desc(sbase + 16384 + 8192, 8192, 1024), db0 = make_desc(sbase, 16, 1024);
  if (BN == 96) { TRC(wg, c.ri, 0); }
#pragma unroll
  for (int j = 0; j < BN / 16; j++) {
    if (j == 4) {
      fence_proxy_async_smem();
      __syncwarp();
      if (lane == 0) mbar_arrive(sbase + OFF_TU0 + wg * 8);
    }
    if (BN == 96) {
      mbar_wait(sbase + OFF_FULL + 128 + (c.nshr & 7) * 8, (c.nshr >> 3) & 1);
      if (j == 0) { TRC(wg, c.ri, 2); }
      c.nshr++;
      wgmma_fence();
#pragma unroll
      for (int k = 0; k < 4; k++) WG<128, 1, 0>::mma(acc4[0], da0 + so + k * 128, db0 + so + k * 2);
      wgmma_commit();
      so = so == (RING_U - 4) * 512 ? 0 : so + 4 * 512;
      if (j) {
        wgmma_wait<1>();
        if ((tid & 127) == 0) mbar_arrive(sbase + OFF_EMPTY + e8);
        e8 = (e8 + 8) & 0x38;
      }
      if (j == 4) mbar_wait(sbase + OFF_SFR, l);
    }
    if (BN == 96 || j == 4) k01 = __uint_as_float(lds32(sbase + OFF_K01));
    else k01 = knext;
    if (BN == 128 && SPREAD) knext = __uint_as_float(lds32(sbase + OFF_K01)); else knext = k01;
#pragma unroll
    for (int b = 0; b < 2; b++)
      stmatrix4(sw[j & 3] + b * 8192 + (j >> 2) * 16384, pack2(gelu_tanh(acc[b][j * 8 + 0], k01), gelu_tanh(acc[b][j * 8 + 1], k01)),
                pack2(gelu_tanh(acc[b][j * 8 + 2], k01), gelu_tanh(acc[b][j * 8 + 3], k01)),
                pack2(gelu_tanh(acc[b][j * 8 + 4], k01), gelu_tanh(acc[b][j * 8 + 5], k01)),
                pack2(gelu_tanh(acc[b][j * 8 + 6], k01), gelu_tanh(acc[b][j * 8 + 7], k01)));
  }
  fence_proxy_async_smem();
  __syncwarp();
  if (lane == 0) mbar_arrive(sbase + OFF_TU1 + wg * 8);
  TRE(wg, l * 32 + 17);
  if (BN == 96) {
    wgmma_wait<0>();
    if ((tid & 127) == 0) mbar_arrive(sbase + OFF_EMPTY + e8);
#pragma unroll
    for (int i = 0; i < 64; i++) asm volatile("" : "+f"(acc4[0][i])::"memory");
    TRC(wg, c.ri, 3);
    c.ri++;
  } else init_down(acc4, xr, sbase);
}

__device__ __forceinline__ void row_stats(const uint4 (&raw)[8], int row0, unsigned tag, int lane) {
  float s[2], q[2];
#pragma unroll
  for (int rr = 0; rr < 2; rr++) {
    s[rr] = 0.f; q[rr] = 0.f;
#pragma unroll
    for (int i = 0; i < 4; i++) {
      float v[8];
      unpack8(raw[rr * 4 + i], v);
      s[rr] += ((v[0] + v[1]) + (v[2] + v[3])) + ((v[4] + v[5]) + (v[6] + v[7]));
#pragma unroll
      for (int e = 0; e < 8; e++) q[rr] = fmaf(v[e], v[e], q[rr]);
    }
  }
#pragma unroll
  for (int o = 16; o > 0; o >>= 1)
#pragma unroll
    for (int rr = 0; rr < 2; rr++) { s[rr] += __shfl_xor_sync(0xffffffffu, s[rr], o); q[rr] += __shfl_xor_sync(0xffffffffu, q[rr], o); }
  const int row = row0 + (lane & 1);
  if (lane < 16)
    __stcg(&g_statsA[((row >> 6) * 8 + (lane >> 1)) * 64 + (row & 63)],
           make_uint4(__float_as_uint(((lane & 1) ? s[1] : s[0]) * 0.125f), tag, __float_as_uint(((lane & 1) ? q[1] : q[0]) * 0.125f), tag));
}
__device__ __forceinline__ uint4 ldg_v(const uint4* p) {
  uint4 v;
  asm volatile("ld.global.nc.v4.u32 {%0,%1,%2,%3}, [%4];" : "=r"(v.x), "=r"(v.y), "=r"(v.z), "=r"(v.w) : "l"(p) : "memory");
  return v;
}
__device__ __noinline__ void startup(const bf16* __restrict__ x, const bf16* __restrict__ wqkv, const bf16* __restrict__ b1,
                                     const bf16* __restrict__ b2, uint32_t sbase, unsigned tag, unsigned delay) {
  const int cta = LCTA, lane = threadIdx.x & 31, wq = __shfl_sync(0xffffffffu, (threadIdx.x >> 5) & 3, 0), m = cta >> 3, j = cta & 7;
  const int i = threadIdx.x & 127, row0 = cta * 8 + wq * 2;
  __nanosleep(delay);
  const uint4* xs = reinterpret_cast<const uint4*>(x + (size_t)row0 * D_DIM) + lane;
  const uint4* ws = reinterpret_cast<const uint4*>(wqkv + (size_t)(j * 128 + wq * 32 + (lane >> 3)) * (3 * D_DIM) + m * 64) + (lane & 7);
  uint4 raw[8], wr[8];
#pragma unroll
  for (int k = 0; k < 8; k++) raw[k] = ldg_v(xs + k * 32);
#pragma unroll
  for (int k = 0; k < 8; k++) wr[k] = ldg_v(ws + k * 4 * 384);
  if (wq < 3) __stcg(&g_cs[j * 1536 + m * 96 + i], make_uint4(0, 0, 0, 0));
  if (wq == 0) {
    if (lane < 28) {
      const int f = lane < 16 ? m * 128 + lane * 8 : 2048 + m * 96 + ((m & 1) ? (lane < 24 ? 32 + (lane - 16) * 8 : (lane - 24) * 8) : (lane - 16) * 8);
      float v[8];
      unpack8(*reinterpret_cast<const uint4*>(b1 + f), v);
#pragma unroll
      for (int e = 0; e < 8; e++) v[e] *= GELU_C;
      sts128(sbase + OFF_B1 + lane * 32, make_uint4(__float_as_uint(v[0]), __float_as_uint(v[1]), __float_as_uint(v[2]), __float_as_uint(v[3])));
      sts128(sbase + OFF_B1 + lane * 32 + 16, make_uint4(__float_as_uint(v[4]), __float_as_uint(v[5]), __float_as_uint(v[6]), __float_as_uint(v[7])));
    }
    if (lane < 16) sts128(sbase + OFF_B2 + lane * 16, *reinterpret_cast<const uint4*>(b2 + ((lane >> 3) * 16 + m) * 64 + (lane & 7) * 8));
  }
  const uint32_t sa = sbase + OFF_STG + 16384;
#define WAITFOR(v) if (v[7].x == tag + v[7].y * 65536 + 12345 && v[6].w == 99) delay++
#define COLSUM(v, p)                                                                                                          \
  {                                                                                                                           \
    float s[8];                                                                                                               \
    _Pragma("unroll") for (int e = 0; e < 8; e++) s[e] = 0.f;                                                                 \
    _Pragma("unroll") for (int k = 0; k < 8; k++) {                                                                           \
      float f[8];                                                                                                             \
      unpack8(v[k], f);                                                                                                       \
      _Pragma("unroll") for (int e = 0; e < 8; e++) s[e] += f[e];                                                             \
    }                                                                                                                         \
    const uint32_t a = sa + (wq * 4 + (lane >> 3)) * 768 + (p) * 256 + (lane & 7) * 32;                                       \
    sts128(a, make_uint4(__float_as_uint(s[0]), __float_as_uint(s[1]), __float_as_uint(s[2]), __float_as_uint(s[3])));       \
    sts128(a + 16, make_uint4(__float_as_uint(s[4]), __float_as_uint(s[5]), __float_as_uint(s[6]), __float_as_uint(s[7])));  \
  }
  uint4 w2[8];
  WAITFOR(raw);
#pragma unroll
  for (int k = 0; k < 8; k++) w2[k] = ldg_v(ws + 128 + k * 4 * 384 + (delay >> 31));
  row_stats(raw, row0, tag, lane);
  WAITFOR(wr);
#pragma unroll
  for (int k = 0; k < 8; k++) raw[k] = ldg_v(ws + 256 + k * 4 * 384 + (delay >> 31));
#pragma unroll 1
  for (int p = 0; p < 3; p++) {
    COLSUM(wr, p);
#pragma unroll
    for (int k = 0; k < 8; k++) { wr[k] = w2[k]; w2[k] = raw[k]; }
  }
  bar_sync(8, 128);
  if (wq < 3) {
    float a = 0.f, b = 0.f;
#pragma unroll
    for (int r = 0; r < 16; r++) { const float2 v = lds64f(sa + r * 768 + i * 8); a += v.x; b += v.y; }
    __stcg(&g_cs[j * 1536 + m * 96 + i], make_uint4(__float_as_uint(a), tag, __float_as_uint(b), tag));
  }
  TRE(1, 24);
#pragma unroll
  for (int k = 0; k < 8; k++) raw[k] = ldg_v(xs + 1024 * 128 + k * 32);
#pragma unroll 1
  for (int q = wq == 3 ? 0 : 1; q < 2; q++) {
    const int tk = q ? i : lane - 32;
    const int row = max(j * 128 + tk, 0);
    const uint4* p = &g_statsA[(row >> 6) * 512 + (row & 63)];
    uint4 v;
    for (int it = 0; it < (1 << 20); it++) {
      v = ld_volatile4(p);
      if (__all_sync(0xffffffffu, v.y == tag && v.w == tag)) break;
      __nanosleep(200);
    }
    const float mean = __uint_as_float(v.x) * (8.0f / D_DIM);
    const float rs = rsqrtf(fmaxf(fmaf(__uint_as_float(v.z), 8.0f / D_DIM, -mean * mean), 0.f) + 1e-5f);
    if (tk >= -16) sts32(sbase + OFF_ST + ((tk & 1) * 72 + 8 + (tk >> 1)) * 4, __float_as_uint(rs));
    if (q) sts128(sbase + OFF_STG + ((i & 64) + (i & 1) * 32 + ((i & 63) >> 1)) * 16, ext_row(mean));
  }
  if (wq < 3) {
    const uint4* p = &g_cs[m * 96 + i];
    uint4 v[8];
    for (int it = 0; it < (1 << 20); it++) {
      bool ok = true;
#pragma unroll
      for (int r = 0; r < 8; r++) v[r] = ld_volatile4(p + r * 1536);
#pragma unroll
      for (int r = 0; r < 8; r++) ok = ok && v[r].y == tag && v[r].w == tag;
      if (__all_sync(0xffffffffu, ok)) break;
      __nanosleep(100);
    }
    float a = 0.f, b = 0.f;
#pragma unroll
    for (int r = 0; r < 8; r++) { a += __uint_as_float(v[r].x); b += __uint_as_float(v[r].z); }
    sts64f(sbase + OFF_CS + i * 8, a, b);
    sts128(sbase + OFF_STG + 2048 + i * 32, ext_col(a));
    sts128(sbase + OFF_STG + 2048 + i * 32 + 16, ext_col(b));
  }
  fence_proxy_async_smem();
  bar_sync(8, 128);
  if (i == 0) mbar_arrive(sbase + OFF_STR);
  TRE(1, 27);
  row_stats(raw, row0 + 1024, tag, lane);
  __syncwarp();
}

__device__ __forceinline__ void poll8(uint4 (&v)[8], const uint4* p, int stride, unsigned tag) {
#pragma unroll 1
  for (int it = 0; it < (1 << 20); it++) {
    bool ok = true;
#pragma unroll
    for (int i = 0; i < 8; i++) v[i] = ld_volatile4(p + i * stride);
#pragma unroll
    for (int i = 0; i < 8; i++) ok = ok && v[i].y == tag && v[i].w == tag;
    if (SKEL || __all_sync(0xffffffffu, ok)) break;
    __nanosleep(200);
  }
}

__global__ void __launch_bounds__(384, 1)
mega_kernel(const __grid_constant__ Params P, const bf16* __restrict__ x, const bf16* __restrict__ wqkv, const bf16* __restrict__ b1,
            const bf16* __restrict__ b2) {
  extern __shared__ __align__(1024) uint8_t smem_raw[];
  const uint32_t sbase = smem_u32(smem_raw);
  if (threadIdx.x == 0) sts128(sbase + OFF_K01, make_uint4(__float_as_uint(GELU_B), 0, logical_cta(), 0x3f800000));
  if (threadIdx.x == 256) {
    for (int s = 0; s < 32; s++) mbar_init(sbase + OFF_FULL + s * 8, 2);
    for (int w = 0; w < 2; w++) {
      mbar_init(sbase + OFF_STR + w * 8, 1); mbar_init(sbase + OFF_RES + w * 8, 1);
      mbar_init(sbase + OFF_OST + w * 8, 4); mbar_init(sbase + OFF_TR + w * 8, 4);
      mbar_init(sbase + OFF_TU0 + w * 8, 4); mbar_init(sbase + OFF_TU1 + w * 8, 4);
    }
    mbar_init(sbase + OFF_SFR, 1);
    for (int s = 0; s < 10; s++) mbar_init(sbase + OFF_DEP + s * 8, 1);
    asm volatile("fence.mbarrier_init.release.cluster;" ::: "memory");
  }
  __syncthreads();

  if (LCTA < 0) {
    if (threadIdx.x == 0) {
      const unsigned epoch = *(volatile unsigned*)&g_epoch;
#pragma unroll 1
      for (int it = 0; it < (1 << 20) && (int)(*(volatile unsigned*)&g_sync[2] - (epoch * 9 + 1) * NCTA) < 0; it++) __nanosleep(2000);
    }
    return;
  }
  const int warp = __shfl_sync(0xffffffffu, threadIdx.x >> 5, 0);
  const int wg = warp >> 2;
  if (__shfl_sync(0xffffffffu, threadIdx.x >> 8, 0) == 0) {
    asm volatile("setmaxnreg.inc.sync.aligned.u32 %0;" ::"n"(RHI));
    TRE(wg, 63);
    TRG(wg, 63);
    const unsigned epoch = *(volatile unsigned*)&g_epoch;
    if (wg == 1) startup(x, wqkv, b1, b2, sbase, epoch * 2 + 1, P.sud);
    Cons c;
    c.nsolo = 0; c.nshr = 0; c.ri = 0;
    float acc4[1][64];
#pragma unroll
    for (int i = 0; i < 64; i++) acc4[0][i] = 0.f;
#pragma unroll 1
    for (int l = -1;; l++) {
      if (l >= 0) {
        uint32_t pk[32];
        gemm_runs<1, 128, 1, 0, 3, 4, 16384, 0, 8192, 0, DP4>(P, sbase, c, acc4, wg);
        TRE(wg, l * 32 + 20);
#pragma unroll
        for (int i = 0; i < 64; i++) acc4[0][i] *= 0.5f / GELU_C;
        const int cta = opaque_cta(), tid = opaque_tid(), lane = tid & 31, rw = ((tid >> 5) & 3) * 16;
#pragma unroll
        for (int j = 0; j < 16; j++) {
          pk[j * 2] = pack2(acc4[0][j * 4 + 0], acc4[0][j * 4 + 1]);
          pk[j * 2 + 1] = pack2(acc4[0][j * 4 + 2], acc4[0][j * 4 + 3]);
        }
        const uint32_t src = sbase + OFF_STG + wg * 16384 + rw * 128;
        stage_tile128(pk, src, lane);
        TRE(wg, l * 32 + 21);
        store_rows(&P.out_s[l], src, (cta & 7) * 128, (wg * 16 + (cta >> 3)) * 64 + rw, sbase + OFF_TR + wg * 8, lane);
        if (l == 0) tile_stats(acc4[0], &g_statsA[(wg * 16 + (cta >> 3)) * 512 + (cta & 7) * 64 + rw + (lane >> 2)], epoch * 2 + 2, lane & 3,
                               __uint_as_float(lds32(sbase + OFF_K01 + 4)));
        TRE(wg, l * 32 + 22);
        if (l) break;
      }
      l++;
      {
        float acc[2][96];
#pragma unroll
        for (int b = 0; b < 2; b++)
#pragma unroll
          for (int i = 0; i < 96; i++) acc[b][i] = 0.f;
        gemm_runs<2, 192, 0, 1, 6, 6, 0, 16384, 0, 0, 1>(P, sbase, c, acc, wg);
        attention(P, acc, sbase, c, wg, l, epoch * 2 + l + 1);
      }
      uint32_t xr[32];
      {
        float acc[1][64];
        {
          if (PREW) {
            const int cta = opaque_cta(), tid = opaque_tid();
            if ((tid & 3) < 2) __stcg(&g_statsB[(wg * 16 + (cta >> 3)) * 512 + (cta & 7) * 64 + ((tid >> 5) & 3) * 16 + ((tid & 31) >> 2) + (tid & 3) * 8], make_uint4(0, 0, 0, 0));
          }
          mbar_wait(sbase + OFF_RES + wg * 8, l);
          const int tid = opaque_tid(), lane = tid & 31, r7 = lane & 7;
          const uint32_t sa = sbase + OFF_STG + wg * 16384 + (((tid >> 5) & 3) * 16 + ((lane >> 3) & 1) * 8 + r7) * 128;
#pragma unroll
          for (int j = 0; j < 8; j++) {
            uint32_t q[4];
            ldmatrix4(q, sa + (j >> 2) * 8192 + ((((j * 2 + (lane >> 4)) & 7) ^ r7) << 4));
#pragma unroll
            for (int i = 0; i < 4; i++) { acc[0][j * 8 + i * 2] = bf_lo(q[i]); acc[0][j * 8 + i * 2 + 1] = bf_hi(q[i]); }
          }
        }
        gemm_runs<1, 128, 0, 1, 3, 3, 16384, 0, 0, 0, DP2>(P, sbase, c, acc, wg);
        TRE(wg, l * 32 + 10);
        const int cta = opaque_cta(), tid = opaque_tid(), lane = tid & 31, rw = ((tid >> 5) & 3) * 16;
        const unsigned tag = epoch * 2 + l + 1;
        uint4* sb = &g_statsB[(wg * 16 + (cta >> 3)) * 512 + rw];
        tile_stats(acc[0], sb + (cta & 7) * 64 + (lane >> 2), tag, lane & 3);
        TRE(wg, l * 32 + 11);
#pragma unroll
        for (int j = 0; j < 16; j++) {
          xr[j * 2] = pack2(acc[0][j * 4 + 0], acc[0][j * 4 + 1]);
          xr[j * 2 + 1] = pack2(acc[0][j * 4 + 2], acc[0][j * 4 + 3]);
        }
        const uint4* sp = sb + (lane & 1) * 256 + (lane >> 1);
        uint4 a, b, cc, d;
        int it = 0;
        __nanosleep(P.pre);
        while (true) {
          a = ld_volatile4(sp); b = ld_volatile4(sp + 64); cc = ld_volatile4(sp + 128); d = ld_volatile4(sp + 192);
          bool ok = a.y == tag && a.w == tag && b.y == tag && b.w == tag && cc.y == tag && cc.w == tag && d.y == tag && d.w == tag;
          if (SKEL || ok || ++it > (1 << 20)) break;
          __nanosleep(P.poll);
        }
        __syncwarp();
        TRE(wg, l * 32 + 12);
        float mean = (__uint_as_float(a.x) + __uint_as_float(b.x)) + (__uint_as_float(cc.x) + __uint_as_float(d.x));
        float v = (__uint_as_float(a.z) + __uint_as_float(b.z)) + (__uint_as_float(cc.z) + __uint_as_float(d.z));
        mean += __shfl_xor_sync(0xffffffffu, mean, 1);
        v += __shfl_xor_sync(0xffffffffu, v, 1);
        mean *= (1.0f / D_DIM);
        v = fmaxf(fmaf(v, 1.0f / D_DIM, -mean * mean), 0.f);
        const float rs = GELU_C * rsqrtf(fmaf(v + 1e-5f, 1e-5f, v));
        mean *= -rs;
        const int g2 = (lane >> 2) * 2;
        const float nm0 = __shfl_sync(0xffffffffu, mean, g2), rs0 = __shfl_sync(0xffffffffu, rs, g2);
        const float nm1 = __shfl_sync(0xffffffffu, mean, g2 + 16), rs1 = __shfl_sync(0xffffffffu, rs, g2 + 16);
        uint32_t hk[32];
#pragma unroll
        for (int j = 0; j < 16; j++) {
          hk[j * 2] = pack2(fmaf(acc[0][j * 4 + 0], rs0, nm0), fmaf(acc[0][j * 4 + 1], rs0, nm0));
          hk[j * 2 + 1] = pack2(fmaf(acc[0][j * 4 + 2], rs1, nm1), fmaf(acc[0][j * 4 + 3], rs1, nm1));
        }
        stage_tile128(hk, sbase + OFF_STG + wg * 16384 + rw * 128, lane);
        TRE(wg, l * 32 + 13);
        fence_proxy_async_smem();
        __syncwarp();
        if (lane == 0) mbar_arrive(sbase + OFF_TR + wg * 8);
      }
      if (wg == 1) mixer_up<96>(P, sbase, c, 1, l, acc4, xr);
      else mixer_up<128>(P, sbase, c, 0, l, acc4, xr);
      l--;
    }
    TRE(wg, 62);
    TRG(wg, 62);
    if ((threadIdx.x & 127) == 0) {
      const unsigned v = atomicAdd(&g_exit, 1);
      if (v == (epoch + 1) * 2 * NCTA - 1) { __threadfence(); *(volatile unsigned*)&g_epoch = epoch + 1; }
    }
  } else {
    asm volatile("setmaxnreg.dec.sync.aligned.u32 %0;" ::"n"(RLO));
    if (warp < 10) {
      if (warp == 8) producer<0>(P, sbase);
      else producer<1>(P, sbase);
    } else {
      const unsigned epoch = __shfl_sync(0xffffffffu, *(volatile unsigned*)&g_epoch, 0);
      const int cta = LCTA, w = warp - 10, m = cta >> 3, j = cta & 7;
      unsigned* const cn = &g_sync[2 + w];
      unsigned tgt = epoch * (9 - 2 * w) * NCTA;
      if (w == 1 && (threadIdx.x & 31) < 19) prefetch_tmap(reinterpret_cast<const CUtensorMap*>(&P) + (threadIdx.x & 31));
      __syncwarp();
#pragma unroll 1
      for (int q9 = 0; q9 < 9; q9++) {
        const int l = q9 >= 5, q = q9 - l * 5;
        if (q == 0 && (w | l)) {
          const int lane = opaque_tid() & 31;
          const uint32_t half = sbase + OFF_STG + (opaque_tid() & 32) * 512;
          mbar_wait(sbase + OFF_OST + 8 - w * 8, w ? l : 0);
#pragma unroll 1
          for (int r = 0; r < 6; r++) sts128(half + 2048 + (r * 32 + lane) * 16, ext_col(__uint_as_float(lds32(sbase + OFF_CS + (r * 32 + lane) * 4))));
#pragma unroll 1
          for (int t0 = -32; t0 < 128; t0 += 32) {
            float mean = 0.f, var = 0.f;
            {
              const int row = max((w * 8 + j) * 128 + t0 + lane, 0);
              uint4 v[8];
              poll8(v, &g_statsA[(row >> 6) * 512 + (row & 63)], 64, epoch * 2 + l + 1);
#pragma unroll
              for (int i = 0; i < 8; i++) { mean += __uint_as_float(v[i].x); var += __uint_as_float(v[i].z); }
            }
            const int tk = t0 + (opaque_tid() & 31);
            mean *= (1.0f / D_DIM);
            const float rs = rsqrtf(fmaxf(fmaf(var, 1.0f / D_DIM, -mean * mean), 0.f) + 1e-5f);
            if (tk >= -16) sts32(sbase + OFF_ST + ((tk & 1) * 72 + 8 + (tk >> 1)) * 4, __float_as_uint(rs));
            if (t0 >= 0) sts128(half + ((tk & 64) + (tk & 1) * 32 + ((tk & 63) >> 1)) * 16, ext_row(mean));
          }
          fence_proxy_async_smem();
          __syncwarp();
          e_arrive(sbase + OFF_STR + w * 8);
          TRA(w, l * 32 + 8);
        }
        const bool isu = q == 2 || q == 3, paced = isu && (w || q == 3), clip = w && q == 3;
        const CUtensorMap* mp = q == 0 ? &P.o_s : q == 1 ? &P.h_m : clip ? &P.u_h : paced ? &P.u_s : &P.u_k;
        uint32_t src = sbase + OFF_STG + (isu ? q - 2 : w) * 16384;
        const int c0 = q == 0 ? m * 64 : !isu ? j * 128 : clip ? 0 : w ? 2048 + m * 96 + (m & 1) * 32 : m * 128 + (q - 2) * 64;
        int c1 = q == 0 ? 0 : isu ? j * 128 : (w * 16 + m) * 64;
        const int c2 = clip ? 64 + m * 3 + 2 - (m & 1) * 2 : 0, c3 = q == 0 ? w * 16 + j * 2 : 0;
        mbar_wait(sbase + OFF_OST + (q == 4 ? 1 : q) * 16 + w * 8, q == 1 ? 0 : q == 4 ? 1 : l);
        TRA(w, l * 32 + (q == 2 ? 25 : 0));
#pragma unroll 1
        for (int pc = paced ? 128 / PROWS : q != 4; pc > 0; pc--) {
          e_tma_store(mp, src, c0, c1, c2, c3);
          bulk_commit();
          bulk_wait_read<PACE>();
          src += PROWS * 128; c1 += PROWS;
        }
        if (w && q == 2) continue;
        bulk_wait<0>();
        TRA(w, l * 32 + ((0x1c001a0e07ull >> (q * 8)) & 31));
        if (q == 3 && !w) e_arrive(sbase + OFF_SFR);
        e_red_release(cn);
        TRA(w, l * 32 + ((0x1713120f09ull >> (q * 8)) & 31));
        if (q == 0) {
          e_tma_load(src - PROWS * 128, &P.xr[l], sbase + OFF_RES + w * 8, j * 128, (w * 16 + m) * 64, 0, 0);
          e_expect_tx(sbase + OFF_RES + w * 8, 16384);
        }
        spin_until(cn, tgt += NCTA);
        e_arrive(sbase + OFF_DEP + (((0x86531 >> (q * 4)) & 15) + w) * 8);
      }
    }
  }
}

typedef CUresult (*PFN_encodeTiled)(CUtensorMap*, CUtensorMapDataType, cuuint32_t, void*, const cuuint64_t*,
                                    const cuuint64_t*, const cuuint32_t*, const cuuint32_t*, CUtensorMapInterleave,
                                    CUtensorMapSwizzle, CUtensorMapL2promotion, CUtensorMapFloatOOBfill);
static PFN_encodeTiled g_encode = nullptr;

static CUtensorMap make_map4(const void* ptr, int d0, int d1, int d2, int d3, int s1, int s2, int s3, int b1, int b2, int b3) {
  CUtensorMap m;
  cuuint64_t dims[4] = {(cuuint64_t)d0, (cuuint64_t)d1, (cuuint64_t)d2, (cuuint64_t)d3};
  cuuint64_t strides[3] = {(cuuint64_t)s1 * 2, (cuuint64_t)s2 * 2, (cuuint64_t)s3 * 2};
  cuuint32_t box[4] = {64, (cuuint32_t)b1, (cuuint32_t)b2, (cuuint32_t)b3};
  cuuint32_t es[4] = {1, 1, 1, 1};
  g_encode(&m, CU_TENSOR_MAP_DATA_TYPE_BFLOAT16, 4, (void*)ptr, dims, strides, box, es, CU_TENSOR_MAP_INTERLEAVE_NONE,
           CU_TENSOR_MAP_SWIZZLE_128B, CU_TENSOR_MAP_L2_PROMOTION_L2_128B, CU_TENSOR_MAP_FLOAT_OOB_FILL_NONE);
  return m;
}
static CUtensorMap make_map(const void* ptr, int rows, int cols, int box_rows, int nblk = 1, int bstep = 64) {
  return make_map4(ptr, cols - (nblk - 1) * bstep, rows, nblk, 1, cols, bstep, 64, box_rows, nblk, 1);
}

#define tune(n, d) (d)
#define PX tune("PX", 8)
#define PA1 tune("PA1", 1)
#define PY tune("PY", 6)
#define PB1 tune("PB1", 0)
#define PZ tune("PZ", 7)
#define PV tune("PV", 4)
#define PA4 tune("PA4", 12)

struct Sched {
  Params& P;
  int pos = 0, e = 0, nr[2] = {0, 0}, l = 0;
  int cap[12] = {8, 8, 8, 8, tune("C2", 8), tune("C2", 8), 8, tune("C3", 8), 8, tune("C4", 8), tune("C4", 8), 8};
  int lastk[2] = {-1, -1}, laste[2] = {0, 0};
  int freeu = RING_U, tail = 0, used[512], cnt[3] = {0, 0, 0};
  Sched(Params& p) : P(p) { P.nseg = 0; }
  void pf(int back, int kind, int k0, int n, int ks = 1) {
    static const int size[12] = {6, 6, 3, 3, 3, 3, 4, 4, 6, 3, 3, 4};
    if (n <= 0) return;
    const uint2 d = make_uint2(kind | k0 << 4 | n << 10 | (ks - 1) << 16 | 1u << 28, 0), o = P.seg[P.nseg - 1];
    const int on = (o.x >> 10) & 63, at = on - back;
    if (back <= 0) { P.seg[P.nseg++] = d; return; }
    if (at <= 0) { P.seg[P.nseg - 1] = d; P.seg[P.nseg++] = o; return; }
    P.seg[P.nseg - 1].x -= back << 10;
    P.seg[P.nseg++] = d;
    uint32_t wc = 0;
    for (int i = 0; i < 14 && i < back; i++) wc |= (at + i < 14 ? (o.y >> (2 * (at + i))) & 3 : 1) << (2 * i);
    P.seg[P.nseg++] = make_uint2((o.x & 0x0801000f) | (((o.x >> 4) & 63) + at * (((o.x >> 16) & 1) + 1)) << 4 | back << 10 |
                                 (((o.x >> 22) & 31) + at * size[o.x & 15]) % RING_U << 22, wc | (((o.y >> 29) + at) & 7) << 29);
  }
  void add(int kind, int k0, int n, int dep, int pre, int post, int fl, int ks = 1, int x = 0) {
    if (n <= 0) return;
    static const int size[12] = {6, 6, 3, 3, 3, 3, 4, 4, 6, 3, 3, 4};
    const int sz = size[kind], sh = kind == K_G3S || kind == K_G4S, w = (kind < K_G3S ? kind : kind - 1) & 1, set = sh ? 2 : w;
    int pad = (pos + sz - 1) / sz * sz - pos;
    pos = (pos + pad) % RING_U;
    for (int v = 0; v < 2; v++)
      if (sh || v == w) {
        const int last = ((fl >> (2 + v)) & 1) | (fl >> 4), drain = ((fl >> v) & 1) | ((fl >> (2 + v)) & 1);
        const int pr = sh && !v ? 0 : pre, po = sh && v ? 0 : post;
        if (nr[v] && lastk[v] == kind && laste[v] == e && !pad && !pr && !(x & (v ? 19 : 3)) && !(P.run[v][nr[v] - 1] & 0x17f80000u) && !tune("NOMERGE", 0)) {
          P.run[v][nr[v] - 1] += n | po << 19 | drain << 23 | last << 24;
          laste[v] = e + n;
          continue;
        }
        lastk[v] = kind; laste[v] = e + n;
        P.run[v][nr[v]++] = n | pos << 6 | (e & 7) << 11 | sh << 14 | (sh && !v ? 0 : pre) << 15 | (sh && v ? 0 : post) << 19 | drain << 23 | last << 24 |
                            (x & 3) << 25 | (kind >= K_G4 ? l : 0) << 27 | (v ? x >> 4 : 0) << 28;
      }
    int i0 = 0;
    const uint32_t px = P.nseg ? P.seg[P.nseg - 1].x : ~0u;
    const uint32_t xf = ((x & 3) ? 2u : 0u) | (x & 12);
    if ((px >> 28) == xf && (int)(px & 15) == kind && !dep && (int)((px >> 16) & 1) == ks - 1 && (int)(((px >> 4) & 63) + ((px >> 10) & 63) * ks) == k0) {
      i0 = (px >> 10) & 63;
      P.seg[P.nseg - 1].x += n << 10;
    } else P.seg[P.nseg++] = make_uint2(kind | k0 << 4 | n << 10 | (ks - 1) << 16 | dep << 17 | pos << 22 | l << 27 | xf << 28, (cnt[set] & 7) << 29);
    for (int i = i0; i < i0 + n; i++) {
      int nw = 0;
      while (freeu < sz + pad || e - tail >= cap[kind]) { freeu += used[tail++]; nw++; }
      if (i >= 14 && nw == 0) { freeu += used[tail++]; nw++; }
      if (nw > 3 || (i >= 14 && nw != 1)) P.nseg = -1000000;
      if (i < 14) P.seg[P.nseg - 1].y |= nw << (2 * i);
      freeu -= used[e++] = sz + pad;
      pad = 0;
    }
    pos = (pos + n * sz) % RING_U;
    cnt[set] += n;
  }
};

static void build_schedule(Params& P) {
  Sched s(P);
  P.map = tune("MAP", 6);
  P.u1d = tune("U1D", 0);
  P.od[0] = tune("OD0", 0);
  P.od[1] = tune("OD1", 0);
  P.u0d = tune("U0D", 0);
  P.sud = tune("SUD", 500);
  P.pre = tune("PRE", 150);
  P.poll = tune("POLL", 40);
  const int pfm = tune("PFM", 0), sk3 = tune("SK3", 0), sk4 = tune("SK4", 5);
  for (int l = 0; l < 2; l++) {
    s.l = l;
    const int b = l * 16, a4 = l ? tune("PA4L", 0) : PA4;
    s.add(K_G1, 0, 13, l ? E_X : 0, 0, 0, 16);
    s.add(K_G1, 13, 3, 0, 0, 1, 0);
    s.add(K_G1 + 1, 0, PA1, l ? E_X + 1 : 0, 1, 0, 3);
    s.add(K_G1 + 1, PA1, PX - PA1, 0, 3, 0, 3);
    s.add(K_G2, 0, 16, b + E_O, 0, 1, 12);
    s.add(K_G1 + 1, PX, 13 - PX, 0, 1, 0, 16);
    const int o3 = tune("OWN3", 1), o3b = tune("OWN3B", 0), o4 = 0;
    s.add(K_G1 + 1, 13, 3, 0, 0, o3 ? 2 : 0, 0);
    s.add(K_G3, 0, o3, 0, 2, 0, 3, 1, 1);
    s.add(K_G3, 0, PY - o3, b + E_H, 4, 0, 3, 1, o3 * 4);
    s.add(K_G2 + 1, 0, 16, b + E_O + 1, 0, 2, 12);
    s.add(K_G3, PY - o3, 16 - PY, 0, 2, 0, 3, 1, o3 * 4);
    s.add(K_G3 + 1, 0, PZ, 0, 0, 0, o3b ? 0 : 3);
    s.add(K_G3S, 16, o3b, 0, 0, 0, 3, 1, 2);
    s.add(K_G3, 16, PV, b + E_H + 1, 0, 0, 0, 1, o3b * 12);
    s.add(K_G3S, 16 + PV, 16 - o3b - PV, PV ? 0 : b + E_H + 1, 0, 0, 4, 1, o3b * 12);
    s.add(K_G3 + 1, PZ, 16 - PZ, 0, 0, 0, PV ? 0 : 12);
    s.add(K_G3 + 1, 16, PV, 0, 0, 0, 12, 1, o3b * 12);
    const int k4 = l ? tune("SK4L", 5) : sk4;
    s.add(K_G4S, 0, 6, b + E_UA, 0, 0, 0, 2, 16);
    s.add(K_G4S, 12, 10, 0, 0, 0, 0, 2);
    int sft = 0;
    while (a4 && (s.pos + (16 - o4 - sft) * 4) % 3) sft++;
    s.add(K_G4S, 1, 16 - o4 - sft, b + E_UB, 0, 0, a4 ? 2 : 0, 2, o4 * 4);
    s.add(K_G4, 32, a4, b + E_U1, 0, 0, 0);
    s.add(K_G4S, 33 - (o4 + sft) * 2, sft, 0, 0, 0, 0, 2, o4 * 4);
    s.add(K_G4S, 32 + a4, 24 - a4 - k4, a4 ? 0 : b + E_U1, 0, 0, k4 ? 2 : a4 ? 4 : 12);
    s.add(K_G4S, 56 - k4, k4, 0, 1, 1, a4 ? 4 : 12);
    s.add(K_G4 + 1, 32, a4, 0, 0, 0, 12);
  }
}

extern "C" void kernel_launch(void* const* d_in, const int* in_sizes, int n_in, void* d_out, int out_size) {
  const bf16* x = (const bf16*)d_in[0];
  const bf16* wqkv = (const bf16*)d_in[1];
  const bf16* wo = (const bf16*)d_in[2];
  const bf16* w1 = (const bf16*)d_in[4];
  const bf16* b1 = (const bf16*)d_in[5];
  const bf16* w2 = (const bf16*)d_in[6];
  const bf16* b2 = (const bf16*)d_in[7];
  bf16* out = (bf16*)d_out;

  if (!g_encode) {
    void* fn = nullptr;
    cudaDriverEntryPointQueryResult st;
    cudaGetDriverEntryPoint("cuTensorMapEncodeTiled", &fn, cudaEnableDefault, &st);
    g_encode = (PFN_encodeTiled)fn;
  }
  bf16 *h, *o, *u, *x2;
  cudaGetSymbolAddress((void**)&h, g_h);
  cudaGetSymbolAddress((void**)&o, g_o);
  cudaGetSymbolAddress((void**)&u, g_u);
  cudaGetSymbolAddress((void**)&x2, g_x2);
  Params P;
  P.xq[0] = make_map4(x, D_DIM, 32, 2, 32, 2 * D_DIM, D_DIM, 64 * D_DIM, 32, 2, 2);
  P.xq[1] = make_map4(x2, D_DIM, 32, 2, 32, 2 * D_DIM, D_DIM, 64 * D_DIM, 32, 2, 2);
  P.o_s = make_map4(o, D_DIM, 32, 2, 32, 2 * D_DIM, D_DIM, 64 * D_DIM, 32, 2, 2);
  P.xr[0] = make_map(x, S_LEN, D_DIM, 64, 2);
  P.xr[1] = make_map(x2, S_LEN, D_DIM, 64, 2);
  P.wqkv = make_map(wqkv, D_DIM, 3 * D_DIM, 64, 3, 1024);
  P.o_k = make_map(o, S_LEN, D_DIM, 64);
  P.wo = make_map(wo, D_DIM, D_DIM, 64, 2);
  P.h_m = make_map(h, S_LEN, D_DIM, 64, 2);
  P.w1a = make_map(w1, S_LEN, F_DIM, 64, 2);
  P.w1b = make_map(w1, S_LEN, F_DIM, 64);
  P.w2s = make_map(w2, F_DIM, S_LEN, 64);
  P.w2d = make_map(w2, F_DIM, S_LEN, 64, 2, 1024);
  P.u_k = make_map(u, D_DIM, F_DIM, 128);
  P.u_s = make_map(u, D_DIM, F_DIM, PROWS);
  P.w1h = make_map4(w1, 32, S_LEN, F_DIM / 32, 1, F_DIM, 32, 64, 64, 1, 1);
  P.u_h = make_map4(u, 32, D_DIM, F_DIM / 32, 1, F_DIM, 32, 64, PROWS, 1, 1);
  P.out_s[0] = make_map(x2, S_LEN, D_DIM, 16);
  P.out_s[1] = make_map(out, S_LEN, D_DIM, 16);
  build_schedule(P);
  cudaFuncSetAttribute(mega_kernel, cudaFuncAttributeMaxDynamicSharedMemorySize, SMEM_TOTAL);
  int sms = 0;
  cudaDeviceGetAttribute(&sms, cudaDevAttrMultiProcessorCount, 0);
  mega_kernel<<<sms == 132 && tune("G132", 1) ? 132 : NCTA, 384, SMEM_TOTAL, cudaStreamPerThread>>>(P, x, wqkv, b1, b2);
}
```

```cpp
#include <cuda_runtime.h>
#include <cuda_bf16.h>
#include <cuda.h>
#include <stdint.h>

typedef __nv_bfloat16 bf16;

#define S_LEN 2048
#define D_DIM 1024
#define F_DIM 3584
#define NCTA 128

__device__ __forceinline__ uint32_t smem_u32(const void* p) { return (uint32_t)__cvta_generic_to_shared(p); }
__device__ __forceinline__ void mbar_init(uint32_t bar, uint32_t count) {
  asm volatile("mbarrier.init.shared::cta.b64 [%0], %1;" ::"r"(bar), "r"(count) : "memory");
}
__device__ __forceinline__ void mbar_arrive(uint32_t bar) {
  asm volatile("mbarrier.arrive.shared::cta.b64 _, [%0];" ::"r"(bar) : "memory");
}
__device__ __forceinline__ void mbar_arrive_n(uint32_t bar, uint32_t n) {
  asm volatile("mbarrier.arrive.shared::cta.b64 _, [%0], %1;" ::"r"(bar), "r"(n) : "memory");
}
__device__ __forceinline__ void mbar_wait(uint32_t bar, uint32_t parity) {
  asm volatile(
      "{\n.reg .pred p;\n.reg .u32 c;\nmov.u32 c, 0;\n"
      "WAIT_LOOP:\n"
      "mbarrier.try_wait.parity.shared::cta.b64 p, [%0], %1;\n"
      "@p bra.uni WAIT_DONE;\n"
      "add.u32 c, c, 1;\n"
      "setp.lt.u32 p, c, 4194304;\n"
      "@p bra.uni WAIT_LOOP;\n"
      "trap;\n"
      "WAIT_DONE:\n}\n" ::"r"(bar), "r"(parity) : "memory");
}
__device__ __forceinline__ void prefetch_tmap(const CUtensorMap* tm) {
  asm volatile("prefetch.tensormap [%0];" ::"l"((uint64_t)tm) : "memory");
}
__device__ __forceinline__ void wgmma_fence() { asm volatile("wgmma.fence.sync.aligned;" ::: "memory"); }
__device__ __forceinline__ void wgmma_commit() { asm volatile("wgmma.commit_group.sync.aligned;" ::: "memory"); }
template <int N>
__device__ __forceinline__ void wgmma_wait() { asm volatile("wgmma.wait_group.sync.aligned %0;" ::"n"(N) : "memory"); }
__device__ __forceinline__ void bar_sync(int id, int nthreads) { asm volatile("bar.sync %0, %1;" ::"r"(id), "r"(nthreads) : "memory"); }
__device__ __forceinline__ void bar_arrive(int id, int nthreads) { asm volatile("bar.arrive %0, %1;" ::"r"(id), "r"(nthreads) : "memory"); }
__device__ __forceinline__ uint64_t make_desc(uint32_t addr, uint32_t lbo_bytes, uint32_t sbo_bytes) {
  uint64_t d = 0;
  d |= (uint64_t)((addr & 0x3FFFF) >> 4);
  d |= (uint64_t)((lbo_bytes & 0x3FFFF) >> 4) << 16;
  d |= (uint64_t)((sbo_bytes & 0x3FFFF) >> 4) << 32;
  d |= (uint64_t)1 << 62;
  return d;
}
template<int TA, int TB>
__device__ __forceinline__ void wgmma_n64(float (&d)[32], uint64_t da, uint64_t db, int scaleD) {
  asm volatile("{\n.reg .pred p;\nsetp.ne.b32 p, %34, 0;\n"
    "wgmma.mma_async.sync.aligned.m64n64k16.f32.bf16.bf16 {%0, %1, %2, %3, %4, %5, %6, %7, %8, %9, %10, %11, %12, %13, %14, %15, %16, %17, %18, %19, %20, %21, %22, %23, %24, %25, %26, %27, %28, %29, %30, %31}, %32, %33, p, 1, 1, %35, %36;\n}\n"
    : "+f"(d[0]), "+f"(d[1]), "+f"(d[2]), "+f"(d[3]), "+f"(d[4]), "+f"(d[5]), "+f"(d[6]), "+f"(d[7]), "+f"(d[8]), "+f"(d[9]), "+f"(d[10]), "+f"(d[11]), "+f"(d[12]), "+f"(d[13]), "+f"(d[14]), "+f"(d[15]), "+f"(d[16]), "+f"(d[17]), "+f"(d[18]), "+f"(d[19]), "+f"(d[20]), "+f"(d[21]), "+f"(d[22]), "+f"(d[23]), "+f"(d[24]), "+f"(d[25]), "+f"(d[26]), "+f"(d[27]), "+f"(d[28]), "+f"(d[29]), "+f"(d[30]), "+f"(d[31])
    : "l"(da), "l"(db), "r"(scaleD), "n"(TA), "n"(TB));
}

template<int TA, int TB>
__device__ __forceinline__ void wgmma_n96(float (&d)[48], uint64_t da, uint64_t db, int scaleD) {
  asm volatile("{\n.reg .pred p;\nsetp.ne.b32 p, %50, 0;\n"
    "wgmma.mma_async.sync.aligned.m64n96k16.f32.bf16.bf16 {%0, %1, %2, %3, %4, %5, %6, %7, %8, %9, %10, %11, %12, %13, %14, %15, %16, %17, %18, %19, %20, %21, %22, %23, %24, %25, %26, %27, %28, %29, %30, %31, %32, %33, %34, %35, %36, %37, %38, %39, %40, %41, %42, %43, %44, %45, %46, %47}, %48, %49, p, 1, 1, %51, %52;\n}\n"
    : "+f"(d[0]), "+f"(d[1]), "+f"(d[2]), "+f"(d[3]), "+f"(d[4]), "+f"(d[5]), "+f"(d[6]), "+f"(d[7]), "+f"(d[8]), "+f"(d[9]), "+f"(d[10]), "+f"(d[11]), "+f"(d[12]), "+f"(d[13]), "+f"(d[14]), "+f"(d[15]), "+f"(d[16]), "+f"(d[17]), "+f"(d[18]), "+f"(d[19]), "+f"(d[20]), "+f"(d[21]), "+f"(d[22]), "+f"(d[23]), "+f"(d[24]), "+f"(d[25]), "+f"(d[26]), "+f"(d[27]), "+f"(d[28]), "+f"(d[29]), "+f"(d[30]), "+f"(d[31]), "+f"(d[32]), "+f"(d[33]), "+f"(d[34]), "+f"(d[35]), "+f"(d[36]), "+f"(d[37]), "+f"(d[38]), "+f"(d[39]), "+f"(d[40]), "+f"(d[41]), "+f"(d[42]), "+f"(d[43]), "+f"(d[44]), "+f"(d[45]), "+f"(d[46]), "+f"(d[47])
    : "l"(da), "l"(db), "r"(scaleD), "n"(TA), "n"(TB));
}

template<int TA, int TB>
__device__ __forceinline__ void wgmma_n128(float (&d)[64], uint64_t da, uint64_t db, int scaleD) {
  asm volatile("{\n.reg .pred p;\nsetp.ne.b32 p, %66, 0;\n"
    "wgmma.mma_async.sync.aligned.m64n128k16.f32.bf16.bf16 {%0, %1, %2, %3, %4, %5, %6, %7, %8, %9, %10, %11, %12, %13, %14, %15, %16, %17, %18, %19, %20, %21, %22, %23, %24, %25, %26, %27, %28, %29, %30, %31, %32, %33, %34, %35, %36, %37, %38, %39, %40, %41, %42, %43, %44, %45, %46, %47, %48, %49, %50, %51, %52, %53, %54, %55, %56, %57, %58, %59, %60, %61, %62, %63}, %64, %65, p, 1, 1, %67, %68;\n}\n"
    : "+f"(d[0]), "+f"(d[1]), "+f"(d[2]), "+f"(d[3]), "+f"(d[4]), "+f"(d[5]), "+f"(d[6]), "+f"(d[7]), "+f"(d[8]), "+f"(d[9]), "+f"(d[10]), "+f"(d[11]), "+f"(d[12]), "+f"(d[13]), "+f"(d[14]), "+f"(d[15]), "+f"(d[16]), "+f"(d[17]), "+f"(d[18]), "+f"(d[19]), "+f"(d[20]), "+f"(d[21]), "+f"(d[22]), "+f"(d[23]), "+f"(d[24]), "+f"(d[25]), "+f"(d[26]), "+f"(d[27]), "+f"(d[28]), "+f"(d[29]), "+f"(d[30]), "+f"(d[31]), "+f"(d[32]), "+f"(d[33]), "+f"(d[34]), "+f"(d[35]), "+f"(d[36]), "+f"(d[37]), "+f"(d[38]), "+f"(d[39]), "+f"(d[40]), "+f"(d[41]), "+f"(d[42]), "+f"(d[43]), "+f"(d[44]), "+f"(d[45]), "+f"(d[46]), "+f"(d[47]), "+f"(d[48]), "+f"(d[49]), "+f"(d[50]), "+f"(d[51]), "+f"(d[52]), "+f"(d[53]), "+f"(d[54]), "+f"(d[55]), "+f"(d[56]), "+f"(d[57]), "+f"(d[58]), "+f"(d[59]), "+f"(d[60]), "+f"(d[61]), "+f"(d[62]), "+f"(d[63])
    : "l"(da), "l"(db), "r"(scaleD), "n"(TA), "n"(TB));
}

template<int TA, int TB>
__device__ __forceinline__ void wgmma_n192(float (&d)[96], uint64_t da, uint64_t db, int scaleD) {
  asm volatile("{\n.reg .pred p;\nsetp.ne.b32 p, %98, 0;\n"
    "wgmma.mma_async.sync.aligned.m64n192k16.f32.bf16.bf16 {%0, %1, %2, %3, %4, %5, %6, %7, %8, %9, %10, %11, %12, %13, %14, %15, %16, %17, %18, %19, %20, %21, %22, %23, %24, %25, %26, %27, %28, %29, %30, %31, %32, %33, %34, %35, %36, %37, %38, %39, %40, %41, %42, %43, %44, %45, %46, %47, %48, %49, %50, %51, %52, %53, %54, %55, %56, %57, %58, %59, %60, %61, %62, %63, %64, %65, %66, %67, %68, %69, %70, %71, %72, %73, %74, %75, %76, %77, %78, %79, %80, %81, %82, %83, %84, %85, %86, %87, %88, %89, %90, %91, %92, %93, %94, %95}, %96, %97, p, 1, 1, %99, %100;\n}\n"
    : "+f"(d[0]), "+f"(d[1]), "+f"(d[2]), "+f"(d[3]), "+f"(d[4]), "+f"(d[5]), "+f"(d[6]), "+f"(d[7]), "+f"(d[8]), "+f"(d[9]), "+f"(d[10]), "+f"(d[11]), "+f"(d[12]), "+f"(d[13]), "+f"(d[14]), "+f"(d[15]), "+f"(d[16]), "+f"(d[17]), "+f"(d[18]), "+f"(d[19]), "+f"(d[20]), "+f"(d[21]), "+f"(d[22]), "+f"(d[23]), "+f"(d[24]), "+f"(d[25]), "+f"(d[26]), "+f"(d[27]), "+f"(d[28]), "+f"(d[29]), "+f"(d[30]), "+f"(d[31]), "+f"(d[32]), "+f"(d[33]), "+f"(d[34]), "+f"(d[35]), "+f"(d[36]), "+f"(d[37]), "+f"(d[38]), "+f"(d[39]), "+f"(d[40]), "+f"(d[41]), "+f"(d[42]), "+f"(d[43]), "+f"(d[44]), "+f"(d[45]), "+f"(d[46]), "+f"(d[47]), "+f"(d[48]), "+f"(d[49]), "+f"(d[50]), "+f"(d[51]), "+f"(d[52]), "+f"(d[53]), "+f"(d[54]), "+f"(d[55]), "+f"(d[56]), "+f"(d[57]), "+f"(d[58]), "+f"(d[59]), "+f"(d[60]), "+f"(d[61]), "+f"(d[62]), "+f"(d[63]), "+f"(d[64]), "+f"(d[65]), "+f"(d[66]), "+f"(d[67]), "+f"(d[68]), "+f"(d[69]), "+f"(d[70]), "+f"(d[71]), "+f"(d[72]), "+f"(d[73]), "+f"(d[74]), "+f"(d[75]), "+f"(d[76]), "+f"(d[77]), "+f"(d[78]), "+f"(d[79]), "+f"(d[80]), "+f"(d[81]), "+f"(d[82]), "+f"(d[83]), "+f"(d[84]), "+f"(d[85]), "+f"(d[86]), "+f"(d[87]), "+f"(d[88]), "+f"(d[89]), "+f"(d[90]), "+f"(d[91]), "+f"(d[92]), "+f"(d[93]), "+f"(d[94]), "+f"(d[95])
    : "l"(da), "l"(db), "r"(scaleD), "n"(TA), "n"(TB));
}

template <int BN, int TA, int TB>
struct WG;
template <int TA, int TB> struct WG<96, TA, TB> { static __device__ __forceinline__ void mma(float (&d)[48], uint64_t a, uint64_t b) { wgmma_n96<TA, TB>(d, a, b, 1); } };
template <int TA, int TB> struct WG<128, TA, TB> { static __device__ __forceinline__ void mma(float (&d)[64], uint64_t a, uint64_t b) { wgmma_n128<TA, TB>(d, a, b, 1); } };
template <int TA, int TB> struct WG<192, TA, TB> { static __device__ __forceinline__ void mma(float (&d)[96], uint64_t a, uint64_t b) { wgmma_n192<TA, TB>(d, a, b, 1); } };

__device__ bf16 g_h[S_LEN * D_DIM];
__device__ bf16 g_o[S_LEN * D_DIM];
__device__ bf16 g_x2[S_LEN * D_DIM];
__device__ bf16 g_u[D_DIM * F_DIM];
__device__ uint4 g_statsA[S_LEN * 8];
__device__ uint4 g_statsB[S_LEN * 8];
__device__ uint4 g_halo[256 * 512];
__device__ uint4 g_cs[8 * 1536];
__device__ __align__(128) unsigned g_sync[32];
#define g_epoch g_sync[0]
#define g_exit g_sync[1]

#define PRE_NS 400
#define POLL_NS 100
#define HALO_NS 40
#define SKEL 0
#define SUD 1000
#define GRP 0
#define U1D 0
#define VAR 1
#define RHI 232
#define RLO 40
#define HOLD 0
#define PNORM 1
#define TV 1
#define FV 1
#define PREW 1
#define EPOLL 1
#define DP2 1
#define DP3A 1
#define DP3B 1
#define DP4 1
#define CK 0
#define P1POLL 0
#define SPREAD 1
#define XT 0
#define PROWS 32
#define PACE 1

#define TRC(wg, r, i)
#define TRG(wg, r)
#define TRE(wg, id)
#define TRA(wg, id)

__device__ __forceinline__ int logical_cta(int emu) {
  uint32_t sm, nsm;
  asm volatile("mov.u32 %0, %smid;" : "=r"(sm));
  asm volatile("mov.u32 %0, %nsmid;" : "=r"(nsm));
  if (gridDim.x == 132 && nsm == 132) {
    int t = sm >> 1;
    if (t == 60 || t == 61) return -1;
    const int g = t < 32 ? t & 7 : t < 60 ? 1 + (t - 32) % 7 : 0;
    const int i = (t < 32 ? t >> 3 : t < 60 ? 4 + (t - 32) / 7 : t - 58) * 2 + (sm & 1);
    const int q = ((emu == 1 ? 0x64752310 : 0x75642310) >> (g * 4)) & 7, p = i >> 1, cp = p % 3;
    return ((q >> 1) * 4 + (cp == 2 ? 3 : p / 3)) * 8 + (q & 1) * 4 + (cp == 2 ? p / 3 : cp) * 2 + (i & 1);
  }
  const int b = blockIdx.x;
  if (b >= NCTA) return -1;
  const int g = b >> 3, i = b & 7, mq = g >> 2, jq = (mq & 1) ? 3 - (g & 3) : (g & 3);
  return ((mq * 4 + (i >> 1)) << 3) + jq * 2 + (i & 1);
}

__device__ __forceinline__ float tanh_fast(float x) {
  float y;
  asm("tanh.approx.f32 %0, %1;" : "=f"(y) : "f"(x));
  return y;
}
#define GELU_C 0.3292034911525734f
#define GELU_B 2.423681954311584f
__device__ __forceinline__ float gelu_tanh(float y, float kb) {
  return fmaf(y, tanh_fast(y * fmaf(y, y, kb)), y);
}
__device__ __forceinline__ float ex2_fast(float x) {
  float y;
  asm("ex2.approx.ftz.f32 %0, %1;" : "=f"(y) : "f"(x));
  return y;
}
__device__ __forceinline__ float rcp_fast(float x) {
  float y;
  asm("rcp.approx.ftz.f32 %0, %1;" : "=f"(y) : "f"(x));
  return y;
}
__device__ __forceinline__ uint32_t pack2(float a, float b) {
  __nv_bfloat162 v = __floats2bfloat162_rn(a, b);
  return *reinterpret_cast<uint32_t*>(&v);
}
__device__ __forceinline__ float bf_lo(uint32_t v) { return __uint_as_float(v << 16); }
__device__ __forceinline__ float bf_hi(uint32_t v) { return __uint_as_float(v & 0xffff0000u); }
__device__ __forceinline__ void unpack8(const uint4& t, float (&f)[8]) {
  f[0] = bf_lo(t.x); f[1] = bf_hi(t.x); f[2] = bf_lo(t.y); f[3] = bf_hi(t.y);
  f[4] = bf_lo(t.z); f[5] = bf_hi(t.z); f[6] = bf_lo(t.w); f[7] = bf_hi(t.w);
}
__device__ __forceinline__ uint4 pack8(const float (&f)[8]) {
  return make_uint4(pack2(f[0], f[1]), pack2(f[2], f[3]), pack2(f[4], f[5]), pack2(f[6], f[7]));
}
__device__ __forceinline__ int opaque_tid() { int v; asm volatile("mov.u32 %0, %tid.x;" : "=r"(v)); return v; }
__device__ __forceinline__ uint4 lds128(uint32_t a) {
  uint4 v;
  asm volatile("ld.shared.v4.u32 {%0,%1,%2,%3}, [%4];" : "=r"(v.x), "=r"(v.y), "=r"(v.z), "=r"(v.w) : "r"(a) : "memory");
  return v;
}
__device__ __forceinline__ float2 lds64f(uint32_t a) {
  float2 v;
  asm volatile("ld.shared.v2.f32 {%0,%1}, [%2];" : "=f"(v.x), "=f"(v.y) : "r"(a) : "memory");
  return v;
}
__device__ __forceinline__ uint32_t lds32(uint32_t a) {
  uint32_t v;
  asm volatile("ld.shared.u32 %0, [%1];" : "=r"(v) : "r"(a) : "memory");
  return v;
}
__device__ __forceinline__ void sts128(uint32_t a, const uint4& v) {
  asm volatile("st.shared.v4.u32 [%0], {%1,%2,%3,%4};" ::"r"(a), "r"(v.x), "r"(v.y), "r"(v.z), "r"(v.w) : "memory");
}
__device__ __forceinline__ void sts32(uint32_t a, uint32_t x) {
  asm volatile("st.shared.u32 [%0], %1;" ::"r"(a), "r"(x) : "memory");
}
__device__ __forceinline__ void sts64(uint32_t a, uint32_t x, uint32_t y) {
  asm volatile("st.shared.v2.u32 [%0], {%1,%2};" ::"r"(a), "r"(x), "r"(y) : "memory");
}
__device__ __forceinline__ void sts64f(uint32_t a, float x, float y) {
  asm volatile("st.shared.v2.f32 [%0], {%1,%2};" ::"r"(a), "f"(x), "f"(y) : "memory");
}
__device__ __forceinline__ void stmatrix4(uint32_t a, uint32_t r0, uint32_t r1, uint32_t r2, uint32_t r3) {
  asm volatile("stmatrix.sync.aligned.m8n8.x4.shared.b16 [%0], {%1,%2,%3,%4};" ::"r"(a), "r"(r0), "r"(r1), "r"(r2), "r"(r3) : "memory");
}
__device__ __forceinline__ void ldmatrix4(uint32_t (&r)[4], uint32_t a) {
  asm volatile("ldmatrix.sync.aligned.m8n8.x4.shared.b16 {%0,%1,%2,%3}, [%4];" : "=r"(r[0]), "=r"(r[1]), "=r"(r[2]), "=r"(r[3]) : "r"(a) : "memory");
}
__device__ __forceinline__ uint32_t movmatrix_t(uint32_t a) {
  uint32_t d;
  asm volatile("movmatrix.sync.aligned.m8n8.trans.b16 %0, %1;" : "=r"(d) : "r"(a));
  return d;
}
__device__ __forceinline__ void mma16816(float (&c)[4], uint32_t a0, uint32_t a1, uint32_t a2, uint32_t a3, uint32_t b0, uint32_t b1) {
  asm volatile("mma.sync.aligned.m16n8k16.row.col.f32.bf16.bf16.f32 {%0,%1,%2,%3}, {%4,%5,%6,%7}, {%8,%9}, {%0,%1,%2,%3};"
               : "+f"(c[0]), "+f"(c[1]), "+f"(c[2]), "+f"(c[3]) : "r"(a0), "r"(a1), "r"(a2), "r"(a3), "r"(b0), "r"(b1));
}
__device__ __forceinline__ void mma1688(float (&c)[4], uint32_t a0, uint32_t a1, uint32_t b0) {
  asm volatile("mma.sync.aligned.m16n8k8.row.col.f32.bf16.bf16.f32 {%0,%1,%2,%3}, {%4,%5}, {%6}, {%0,%1,%2,%3};"
               : "+f"(c[0]), "+f"(c[1]), "+f"(c[2]), "+f"(c[3]) : "r"(a0), "r"(a1), "r"(b0));
}
__device__ __forceinline__ uint4 ld_volatile4(const uint4* p) {
  uint4 v;
  asm volatile("ld.relaxed.gpu.global.v4.u32 {%0,%1,%2,%3}, [%4];" : "=r"(v.x), "=r"(v.y), "=r"(v.z), "=r"(v.w) : "l"(p) : "memory");
  return v;
}
__device__ __forceinline__ void stg128(bf16* p, uint32_t a, uint32_t b, uint32_t c, uint32_t d) {
  asm volatile("st.global.v4.u32 [%0], {%1,%2,%3,%4};" ::"l"(p), "r"(a), "r"(b), "r"(c), "r"(d) : "memory");
}
__device__ __forceinline__ void quad_transpose(uint32_t& p0, uint32_t& p1, uint32_t& p2, uint32_t& p3, int t) {
  const bool odd = t & 1, hi = t & 2;
  const uint32_t r0 = __shfl_xor_sync(0xffffffffu, odd ? p0 : p1, 1), r1 = __shfl_xor_sync(0xffffffffu, odd ? p2 : p3, 1);
  const uint32_t ae = odd ? r0 : p0, ao = odd ? p1 : r0, be = odd ? r1 : p2, bo = odd ? p3 : r1;
  const uint32_t v0 = __shfl_xor_sync(0xffffffffu, hi ? ae : be, 2), v1 = __shfl_xor_sync(0xffffffffu, hi ? ao : bo, 2);
  p0 = hi ? v0 : ae; p1 = hi ? v1 : ao; p2 = hi ? be : v0; p3 = hi ? bo : v1;
}
__device__ __forceinline__ void fence_proxy_async_smem() { asm volatile("fence.proxy.async.shared::cta;" ::: "memory"); }
__device__ __forceinline__ void spin_until(const unsigned* p, unsigned target) {
  asm volatile(
      "{\n.reg .pred p;\n.reg .u32 v, c;\nmov.u32 c, 0;\n"
      "SPIN_LOOP:\n"
      "ld.relaxed.gpu.global.u32 v, [%0];\n"
      "sub.u32 v, v, %1;\n"
      "setp.ge.s32 p, v, 0;\n"
      "@p bra.uni SPIN_DONE;\n"
      "add.u32 c, c, 1;\n"
      "setp.lt.u32 p, c, 4194304;\n"
      "@p bra.uni SPIN_LOOP;\n"
      "trap;\n"
      "SPIN_DONE:\n"
      "fence.acquire.gpu;\n}\n" ::"l"(p), "r"(target) : "memory");
}
__device__ __forceinline__ void e_expect_tx(uint32_t bar, uint32_t bytes) {
  asm volatile("{\n.reg .pred p;\nelect.sync _|p, 0xffffffff;\n@p mbarrier.arrive.expect_tx.shared::cta.b64 _, [%0], %1;\n}\n" ::"r"(bar), "r"(bytes) : "memory");
}
__device__ __forceinline__ void e_tma_load(uint32_t dst, const CUtensorMap* tm, uint32_t bar, int c0, int c1, int c3, int c4, uint64_t pol) {
  asm volatile(
      "{\n.reg .pred p;\nelect.sync _|p, 0xffffffff;\n"
      "@p cp.async.bulk.tensor.5d.shared::cluster.global.mbarrier::complete_tx::bytes.L2::cache_hint [%0], [%1, {%3, %4, %5, %6, %7}], [%2], %8;\n}\n" ::"r"(dst),
      "l"((uint64_t)tm), "r"(bar), "r"(c0), "r"(c1), "r"(0), "r"(c3), "r"(c4), "l"(pol) : "memory");
}
#define POL_NORMAL 0x1000000000000000ull
#define POL_FIRST 0x12F0000000000000ull
__device__ __forceinline__ void e_arrive(uint32_t bar) {
  asm volatile("{\n.reg .pred p;\nelect.sync _|p, 0xffffffff;\n@p mbarrier.arrive.shared::cta.b64 _, [%0];\n}\n" ::"r"(bar) : "memory");
}
__device__ __forceinline__ void e_red_release(unsigned* p) {
  asm volatile("{\n.reg .pred p;\nfence.proxy.async;\nelect.sync _|p, 0xffffffff;\n@p red.relaxed.gpu.global.add.u32 [%0], 1;\n}\n" ::"l"(p) : "memory");
}

#define RING_U 28
#define OFF_EXT (25 * 8192)
#define OFF_HALO (OFF_EXT + 10240)
#define OFF_BAR (RING_U * 8192)
#define RING_LIM(c) ((0x1c1918 >> ((c) * 8)) & 31)
#define OFF_FULL (OFF_BAR)
#define OFF_EMPTY (OFF_BAR + 192)
#define OFF_STR (OFF_BAR + 256)
#define OFF_OST (OFF_BAR + 272)
#define OFF_TR (OFF_BAR + 288)
#define OFF_TU0 (OFF_BAR + 304)
#define OFF_TU1 (OFF_BAR + 320)
#define OFF_SFR (OFF_BAR + 336)
#define OFF_K01 (OFF_BAR + 352)
#define OFF_RES (OFF_BAR + 368)
#define OFF_DEP (OFF_B2 + 256)
#define OFF_CS (OFF_BAR + 384)
#define OFF_ST (OFF_CS + 768)
#define OFF_B1 (OFF_ST + 576)
#define OFF_B2 (OFF_B1 + 640)
#define SMEM_TOTAL (OFF_B2 + 256 + 80)

enum { K_G1 = 0, K_RES = 2, K_G2 = 4, K_G3 = 6, K_G3S = 8, K_G4 = 9, K_G4S = 11 };
enum { E_O = 1, E_H = 3, E_UA = 5, E_UB = 6, E_U1 = 7, E_X = 8 };
#define MAXSEG 80
#define MAXRUN 56

struct Params {
  CUtensorMap xq[2], wqkv, o_k, wo, h_m, h_1, w1a, w1b, w2, u_k;
  uint2 seg[MAXSEG];
  uint32_t run[2][MAXRUN];
  int nseg;
  uint32_t pre, poll, u0d, u1d, sud, map, rsd, ef[2], npace;
};

#define LCTA __shfl_sync(0xffffffffu, (int)lds32(sbase + OFF_K01 + 8), 0)
#define opaque_cta() LCTA

template <int WHICH>
__device__ __forceinline__ void producer(const Params& P, uint32_t sbase) {
  const int cta = LCTA, m = cta >> 3, j = cta & 7;
  uint32_t tail8 = 0;
  unsigned ptgt = 0;
  const int nseg = P.nseg;
#pragma unroll 1
  for (int si = 0; si < nseg; si++) {
    const uint32_t sg = P.seg[si].x;
    const int kind = sg & 15, n = (sg >> 10) & 63, ks = (((sg >> 16) & 1) + 1) * 64, dep = (sg >> 17) & 31, l = (sg >> 27) & 1;
    const int kk = ((sg >> 4) & 63) * 64;
    const int w = (kind < K_G3S ? kind : kind - 1) & 1;
    const int set = kind == K_G4S ? 2 : w;
    const CUtensorMap* mp;
    int c0 = kk, c1 = kk, c3 = 0, c4 = 0, d0 = 0, d1 = ks, d4 = 0, dx = 0, size, soff;
    uint32_t bytes;
    if (kind < K_G2) {
      size = 5;
      if (WHICH == 0) { mp = &P.wqkv; c0 = m * 64; soff = 16384; bytes = 24576; }
      else { mp = &P.xq[l]; c1 = 0; c3 = w * 16 + j * 2; d0 = ks; d1 = 0; soff = 0; bytes = 16384; }
    } else if (kind < K_G3) {
      size = 3;
      if (WHICH == 0) { mp = &P.wo; c0 = j * 128; c1 = 0; c4 = kk >> 5; d1 = 0; d4 = ks >> 5; dx = 64; soff = 0; bytes = 16384; }
      else { mp = &P.o_k; c1 = (w * 16 + m) * 64; d0 = ks; d1 = 0; soff = 16384; bytes = 8192; }
    } else if (kind < K_G4) {
      size = 4;
      if (WHICH == 0) {
        if (w) { mp = &P.w1b; c0 = 2048 + (m >> 1) * 192; soff = 8192; bytes = 24576; }
        else { mp = &P.w1a; c0 = m * 128; soff = 16384; bytes = 16384; }
      } else {
        soff = 0;
        if (w) { mp = &P.h_1; c0 = j * 128 + (m & 1) * 64; bytes = 8192; }
        else { mp = &P.h_m; c0 = j * 128; bytes = 16384; }
      }
    } else {
      size = kind == K_G4S ? 4 : 3;
      if (WHICH == 0) {
        mp = &P.w2; c1 = 0; c4 = kk >> 5; d1 = 0; d4 = ks >> 5; soff = 16384;
        if (kind == K_G4S) { c0 = m * 64; dx = 1024; bytes = 16384; }
        else { c0 = (w * 16 + m) * 64; bytes = 8192; }
      } else { mp = &P.u_k; c1 = j * 128; d0 = ks; d1 = 0; soff = 0; bytes = 16384; }
    }
    const uint64_t pol = ((P.ef[WHICH] >> (kind + l * 12)) & 1) ? POL_FIRST : POL_NORMAL;
    uint32_t wc = P.seg[si].y;
    const uint32_t fb0 = sbase + OFF_FULL + set * 64, dst0 = sbase + soff, step = size * 8192,
                   dlim = dst0 + (RING_LIM((sg >> 29) & 3) - size) * 8192;
    uint32_t fb = fb0 + (wc >> 29) * 8, dst = dst0 + ((sg >> 22) & 31) * 8192;
    wc = (wc & 0x0fffffffu) | 0x50000000u;
    if (WHICH == 1 && ((sg >> 28) & 1)) {
      asm volatile("{\n.reg .pred p;\nelect.sync _|p, 0xffffffff;\n@p red.relaxed.gpu.global.add.u32 [%0], 1;\n}\n" ::"l"(&g_sync[4]) : "memory");
      spin_until(&g_sync[4], (lds32(sbase + OFF_SFR) * P.npace + ++ptgt) * NCTA);
    }
    if (WHICH == 1 && !SKEL && dep) {
      mbar_wait(sbase + OFF_DEP + (dep & 15) * 8, dep >> 4);
      asm volatile("fence.proxy.async.global;" ::: "memory");
    }
#pragma unroll 1
    for (int i = n; i > 0; i--) {
#pragma unroll 1
      for (uint32_t q = wc & 3; q; q--) {
        mbar_wait(sbase + OFF_EMPTY + (tail8 & 0x38), (tail8 >> 6) & 1);
        tail8 += 8;
      }
      e_tma_load(dst, mp, fb, c0, c1, c3, c4, pol);
      if (WHICH == 0 && dx) e_tma_load(dst + 8192, mp, fb, c0 + dx, c1, c3, c4, pol);
      e_expect_tx(fb, bytes);
      wc = (wc >> 2) | 0x40000000u;
      c0 += d0; c1 += d1; c4 += d4;
      fb = fb == fb0 + 56 ? fb0 : fb + 8;
      dst += step;
      if (dst > dlim) dst = dst0;
    }
  }
}

struct Cons {
  uint32_t nsolo, nshr;
  int ri;
  uint32_t prev;
};
template <int MW, int BN, int TA, int TB, int SZ0, int SZ1, int AOFF, int BOFF, int ASH, int BSH, int DP>
__device__ __forceinline__ void gemm_runs(const Params& P, uint32_t sbase, Cons& c, float (&acc)[MW][BN / 2], int wg) {
  uint32_t prev = 0, prev2 = 0;
  uint32_t r;
#pragma unroll
  for (int b = 0; b < MW; b++)
#pragma unroll
    for (int i = 0; i < BN / 2; i++) asm volatile("" : "+f"(acc[b][i])::"memory");
  const bool lead = (threadIdx.x & 127) == 0;
  if (DP == 2) { wgmma_fence(); wgmma_commit(); wgmma_commit(); }
#pragma unroll 1
  do {
    r = P.run[wg][c.ri];
    const int sh = (r >> 14) & 1, pre = (r >> 15) & 15, post = (r >> 19) & 15;
    uint32_t so = ((r >> 6) & 31) * 512, e8 = (r >> 8) & 0x38;
    const uint32_t size = (sh ? SZ1 : SZ0) * 512, slim = RING_LIM((r >> 25) & 3) * 512 - size;
    uint32_t cnt = sh ? c.nshr : c.nsolo;
    const uint32_t fb0 = sbase + OFF_FULL + (sh ? 2 : wg) * 64, eb0 = sbase + OFF_EMPTY + 2 - sh;
    const uint64_t da0 = make_desc(sbase + AOFF + (sh ? ASH * wg : 0), TA ? 8192 : 16, 1024);
    const uint64_t db0 = make_desc(sbase + BOFF + (sh ? BSH * wg : 0), TB ? 8192 : 16, 1024);
    TRC(wg, c.ri, 0);
    if (pre) bar_sync(pre, 256);
    int i = r & 63;
#pragma unroll 1
    do {
      mbar_wait(fb0 + (cnt & 7) * 8, (cnt >> 3) & 1);
      wgmma_fence();
#pragma unroll
      for (int k = 0; k < 4; k++) {
#pragma unroll
        for (int b = 0; b < MW; b++)
          WG<BN, TA, TB>::mma(acc[b], da0 + so + b * 512 + (TA ? k * 128 : k * 2), db0 + so + (TB ? k * 128 : k * 2));
        if (k == (DP == 3 ? CK : 3)) wgmma_commit();
      }
      if (post && i == 1) bar_arrive(post, 256);
      cnt++;
      so += size;
      if (so > slim) so = 0;
      wgmma_wait<DP == 2 ? 2 : 1>();
      const uint32_t rel = DP >= 2 ? prev2 : prev;
      if (rel && lead) mbar_arrive_n(rel & ~7u, rel & 7);
      prev2 = prev;
      prev = eb0 + e8;
      e8 = (e8 + 8) & 0x38;
    } while (--i);
    if (sh) c.nshr = cnt; else c.nsolo = cnt;
    if (r & (1u << 23)) {
      if (DP == 3) wgmma_commit();
      wgmma_wait<0>();
      if (DP >= 2 && prev2 && lead) mbar_arrive_n(prev2 & ~7u, prev2 & 7);
      if (lead) mbar_arrive_n(prev & ~7u, prev & 7);
      prev = prev2 = 0;
    }
    TRC(wg, c.ri, 3);
    c.ri++;
  } while (!(r & (1u << 24)));
  if (BN == 192 && !TA) { c.prev = prev & ~7u; return; }
  if (DP == 3) wgmma_commit();
  wgmma_wait<0>();
#pragma unroll
  for (int b = 0; b < MW; b++)
#pragma unroll
    for (int i = 0; i < BN / 2; i++) asm volatile("" : "+f"(acc[b][i])::"memory");
}

__device__ __forceinline__ void store_tile128(const uint32_t (&pk)[32], bf16* dst, uint32_t bar, int lane) {
#pragma unroll
  for (int i = 0; i < 8; i++) {
    const int o = (i >> 1) * 8 + (i & 1);
    stg128(dst + (i & 1) * 8 * D_DIM + (i >> 1) * 32, pk[o], pk[o + 2], pk[o + 4], pk[o + 6]);
  }
  __syncwarp();
  e_arrive(bar);
}
__device__ __forceinline__ void tile_stats(const float (&acc)[64], uint4* dst, unsigned tag, int t, float z = 0.f) {
  float s0 = z, s1 = z, s2 = z, s3 = z, q0 = z, q1 = z, q2 = z, q3 = z;
#pragma unroll
  for (int j = 0; j < 16; j++) {
    s0 += acc[j * 4 + 0]; s2 += acc[j * 4 + 1]; s1 += acc[j * 4 + 2]; s3 += acc[j * 4 + 3];
    q0 = fmaf(acc[j * 4 + 0], acc[j * 4 + 0], q0); q2 = fmaf(acc[j * 4 + 1], acc[j * 4 + 1], q2);
    q1 = fmaf(acc[j * 4 + 2], acc[j * 4 + 2], q1); q3 = fmaf(acc[j * 4 + 3], acc[j * 4 + 3], q3);
  }
  s0 += s2; s1 += s3; q0 += q2; q1 += q3;
  float s = (t & 1) ? s1 : s0, q = (t & 1) ? q1 : q0;
  s += __shfl_xor_sync(0xffffffffu, (t & 1) ? s0 : s1, 1); q += __shfl_xor_sync(0xffffffffu, (t & 1) ? q0 : q1, 1);
  s += __shfl_xor_sync(0xffffffffu, s, 2); q += __shfl_xor_sync(0xffffffffu, q, 2);
  if (t < 2) __stcg(dst + t * 8, make_uint4(__float_as_uint(s), tag, __float_as_uint(q), tag));
}

__device__ __forceinline__ void attention(const Params& P, float (&acc)[2][96], uint32_t sbase, Cons& c, int wg, int l, unsigned tag) {
  const uint32_t r = P.run[wg][c.ri];
  const uint32_t slot0 = sbase + OFF_HALO - 4096;
  TRC(wg, c.ri, 0);
        if (PREW) {
          const int cta = opaque_cta(), tid = opaque_tid();
          if (tid & 32) {
            uint4* hp = &g_halo[((wg * 8 + (cta & 7)) * 16 + (cta >> 3)) * 512 + ((tid >> 6) & 1) * 256 + (tid & 31)];
#pragma unroll
            for (int i = 0; i < 8; i++) __stcg(hp + i * 32, make_uint4(0, 0, 0, 0));
          }
        }
  const uint64_t da0 = make_desc(sbase, 16, 1024), db0 = make_desc(sbase + 16384, 8192, 1024);
  const uint32_t so0 = ((r >> 6) & 31) * 512, so1 = so0 > 15 * 512 ? 0 : so0 + 5 * 512, so2 = so1 > 15 * 512 ? 0 : so1 + 5 * 512;
  {
    uint32_t so = so0;
#pragma unroll 1
    for (int i = 0; i < 3; i++) {
      mbar_wait(sbase + OFF_FULL + wg * 64 + (c.nsolo & 7) * 8, (c.nsolo >> 3) & 1);
      if (i == 0) TRC(wg, c.ri, 2);
      c.nsolo++;
      wgmma_fence();
#pragma unroll
      for (int k = 0; k < 4; k++) WG<192, 0, 1>::mma(acc[1], da0 + so + 512 + k * 2, db0 + so + k * 128);
      wgmma_commit();
      wgmma_wait<1>();
      if (i == 0 && (threadIdx.x & 127) == 0) mbar_arrive_n(c.prev, 2);
      so = so > 15 * 512 ? 0 : so + 5 * 512;
    }
  }
#define TAIL(so)                                                                                                           \
  _Pragma("unroll") for (int k = 0; k < 4; k++) WG<192, 0, 1>::mma(acc[0], da0 + (so) + k * 2, db0 + (so) + k * 128);      \
  wgmma_commit()
#define EB(i) (sbase + OFF_EMPTY + (((r >> 11) + (i)) & 7) * 8)
#define PIN(b, i0, i1) _Pragma("unroll") for (int i = i0; i < i1; i++) asm volatile("" : "+f"(acc[b][i])::"memory")
#define PK(b, jj, h) pack2(acc[b][(jj) * 4 + (h) * 2], acc[b][(jj) * 4 + (h) * 2 + 1])
  mbar_wait(sbase + OFF_STR + wg * 8, l);
  {
    const uint64_t de = (uint64_t)(((sbase + OFF_EXT + wg * 5120) & 0x3FFFF) >> 4) | ((uint64_t)8 << 32);
    wgmma_fence();
    wgmma_n192<0, 0>(acc[1], de + 64, de + 128, 1);
    wgmma_commit();
    wgmma_n192<0, 0>(acc[0], de, de + 128, 1);
  }
  TAIL(so0);
  TAIL(so1);
  const int cta = opaque_cta(), tid = opaque_tid(), lane = tid & 31, g = lane >> 2, t = lane & 3;
  const int wq = __shfl_sync(0xffffffffu, (tid >> 5) & 3, 0), hf = wq & 1;
  const int T = wg * 8 + (cta & 7), tn = cta >> 3;
  uint4* const hp = &g_halo[(T * 16 + tn) * 512 + (wq >> 1) * 256 + lane];
  uint32_t Q[2][8][2], K[2][8][2], V[2][8][2];
#define PACKKV(b)                                                                                       \
  _Pragma("unroll") for (int jj = 7; jj >= 0; jj--) {                                                   \
    V[b][jj][1] = movmatrix_t(PK(b, jj + 16, 1)); V[b][jj][0] = PK(b, jj + 16, 0);                      \
  }                                                                                                     \
  _Pragma("unroll") for (int jj = 7; jj >= 0; jj--) { K[b][jj][1] = PK(b, jj + 8, 1); K[b][jj][0] = PK(b, jj + 8, 0); }
#define PACKQ(b)                                                                                        \
  _Pragma("unroll") for (int jj = 7; jj >= 0; jj--) {                                                   \
    V[b][jj][0] = movmatrix_t(V[b][jj][0]); Q[b][jj][1] = PK(b, jj, 1); Q[b][jj][0] = PK(b, jj, 0);     \
  }
#define HALO_OUT(b, a)                                                                                  \
  sts128(a, make_uint4(K[b][0][1], K[b][1][1], K[b][2][1], K[b][3][1]));                                \
  sts128(a + 512, make_uint4(K[b][4][1], K[b][5][1], K[b][6][1], K[b][7][1]));                          \
  sts128(a + 1024, make_uint4(V[b][0][1], V[b][1][1], V[b][2][1], V[b][3][1]));                         \
  sts128(a + 1536, make_uint4(V[b][4][1], V[b][5][1], V[b][6][1], V[b][7][1]))
  wgmma_wait<TV ? 2 : 3>();
  PIN(1, 0, 96);
  TRE(wg, l * 32 + 1);
  PACKKV(1);
  if (!hf) { HALO_OUT(1, slot0 + (5 + wq) * 2048 + lane * 16); }
  else if (T < 15) {
#pragma unroll
    for (int i = 0; i < 4; i++) {
      __stcg(hp + i * 32, make_uint4(K[1][i * 2][1], tag, K[1][i * 2 + 1][1], tag));
      __stcg(hp + (i + 4) * 32, make_uint4(V[1][i * 2][1], tag, V[1][i * 2 + 1][1], tag));
    }
  }
  TRE(wg, l * 32 + 2);
  wgmma_fence();
  TAIL(so2);
  wgmma_wait<2>();
  if ((tid & 127) == 0) mbar_arrive_n(EB(0), 2);
  PACKQ(1);
  wgmma_wait<1>();
  if ((r >> 19) & 15) bar_arrive((r >> 19) & 15, 256);
  if ((tid & 127) == 0) mbar_arrive_n(EB(1), 2);
  const bool o0 = 2 * t > g, o1 = 2 * t + 1 > g;
  float rk[2][4], rq[2][4];
#pragma unroll
  for (int b = 0; b < 2; b++) {
    const uint32_t a = sbase + OFF_ST + ((wq >> 1) * 72 + 8 + b * 32 + hf * 16) * 4;
    const float kscale = 0.17677669529663687f * 1.4426950408889634f;
    const float q0 = __uint_as_float(lds32(a + g * 4)) * kscale, q1 = __uint_as_float(lds32(a + g * 4 + 32)) * kscale;
    const uint32_t a0 = a + t * 8 - (o0 ? 32 : 0), a1 = a + t * 8 + 4 - (o1 ? 32 : 0);
    rk[b][0] = __uint_as_float(lds32(a0)); rk[b][1] = __uint_as_float(lds32(a1));
    rk[b][2] = __uint_as_float(lds32(a0 + 32)); rk[b][3] = __uint_as_float(lds32(a1 + 32));
    rq[b][0] = rk[b][0] * q0; rq[b][1] = rk[b][1] * q0; rq[b][2] = rk[b][2] * q1; rq[b][3] = rk[b][3] * q1;
  }
  const bool remote = !hf && T > 0 && !SKEL;
  uint4 hv[8];
#pragma unroll
  for (int i = 0; i < 8; i++)
    asm volatile("{\n.reg .pred p;\nsetp.ne.u32 p, %5, 0;\nmov.u32 %0, 0;\nmov.u32 %1, 0;\nmov.u32 %2, 0;\nmov.u32 %3, 0;\n"
                 "@p ld.relaxed.gpu.global.v4.u32 {%0,%1,%2,%3}, [%4];\n}\n"
                 : "=&r"(hv[i].x), "=&r"(hv[i].y), "=&r"(hv[i].z), "=&r"(hv[i].w) : "l"(hp - 16 * 512 + i * 32), "r"((int)remote) : "memory");
  wgmma_wait<0>();
  PIN(0, 0, 96);
  if ((tid & 127) == 0) mbar_arrive_n(EB(2), 2);
  TRC(wg, c.ri, 3);
  c.ri++;
  PACKKV(0);
  HALO_OUT(0, slot0 + (hf ? 3 + wq : 2 + (wq >> 1)) * 2048 + lane * 16);
  PACKQ(0);
  TRE(wg, l * 32 + 29);
  bar_sync(7 + wg, 128);
  uint32_t HK[2][8], HV[2][8];
#pragma unroll
  for (int b = 1; b >= 0; b--) {
    if (b == 1 || hf) {
      const uint32_t a = slot0 + (b ? 4 + wq : 2 + (wq >> 1)) * 2048 + lane * 16;
      const uint4 k0 = lds128(a), k1 = lds128(a + 512), v0 = lds128(a + 1024), v1 = lds128(a + 1536);
      HK[b][0] = k0.x; HK[b][1] = k0.y; HK[b][2] = k0.z; HK[b][3] = k0.w; HK[b][4] = k1.x; HK[b][5] = k1.y; HK[b][6] = k1.z; HK[b][7] = k1.w;
      HV[b][0] = v0.x; HV[b][1] = v0.y; HV[b][2] = v0.z; HV[b][3] = v0.w; HV[b][4] = v1.x; HV[b][5] = v1.y; HV[b][6] = v1.z; HV[b][7] = v1.w;
    } else {
      if (remote) {
#pragma unroll 1
        for (int it = 0; it < (1 << 20); it++) {
          bool ok = true;
#pragma unroll
          for (int i = 0; i < 8; i++) ok = ok && hv[i].y == tag && hv[i].w == tag;
          if (__all_sync(0xffffffffu, ok)) break;
          __nanosleep(HALO_NS);
#pragma unroll
          for (int i = 0; i < 8; i++) hv[i] = ld_volatile4(hp - 16 * 512 + i * 32);
        }
      }
#pragma unroll
      for (int i = 0; i < 4; i++) { HK[0][i * 2] = hv[i].x; HK[0][i * 2 + 1] = hv[i].z; HV[0][i * 2] = hv[i + 4].x; HV[0][i * 2 + 1] = hv[i + 4].z; }
    }
  }
  TRE(wg, l * 32 + 3);
  float S[2][2][3][4];
#pragma unroll
  for (int b = 1; b >= 0; b--)
#pragma unroll
    for (int u = 0; u < 2; u++)
#pragma unroll
      for (int kt = 0; kt < 3; kt++) S[b][u][kt][0] = S[b][u][kt][1] = S[b][u][kt][2] = S[b][u][kt][3] = 0.f;
#pragma unroll
  for (int ks = 0; ks < 2; ks++)
#pragma unroll
    for (int b = 1; b >= 0; b--)
#pragma unroll
      for (int u = 0; u < 2; u++) {
        const int j0 = u * 4 + ks * 2;
        mma16816(S[b][u][1], Q[b][j0][0], Q[b][j0][1], Q[b][j0 + 1][0], Q[b][j0 + 1][1], K[b][j0][0], K[b][j0 + 1][0]);
        mma16816(S[b][u][2], Q[b][j0][0], Q[b][j0][1], Q[b][j0 + 1][0], Q[b][j0 + 1][1], K[b][j0][1], K[b][j0 + 1][1]);
        mma16816(S[b][u][0], Q[b][j0][0], Q[b][j0][1], Q[b][j0 + 1][0], Q[b][j0 + 1][1], HK[b][j0], HK[b][j0 + 1]);
      }
  TRE(wg, l * 32 + 4);
  const uint32_t mold = (o0 ? 0xffffu : 0u) | (o1 ? 0xffff0000u : 0u);
  const float NEG = -3.0e38f;
  const bool first = T == 0 && !hf;
  uint32_t pl[2][2], ph[2][2];
#pragma unroll
  for (int b = 1; b >= 0; b--)
#pragma unroll
    for (int u = 0; u < 2; u++) {
      float a0 = (o0 ? S[b][u][0][0] : S[b][u][1][0]) * rq[b][0], a1 = (o1 ? S[b][u][0][1] : S[b][u][1][1]) * rq[b][1];
      float b0 = (o0 ? S[b][u][1][2] : S[b][u][2][2]) * rq[b][2], b1 = (o1 ? S[b][u][1][3] : S[b][u][2][3]) * rq[b][3];
      if (b == 0) { a0 = (first && o0) ? NEG : a0; a1 = (first && o1) ? NEG : a1; }
      float m0 = fmaxf(a0, a1), m1 = fmaxf(b0, b1);
      m0 = fmaxf(m0, __shfl_xor_sync(0xffffffffu, m0, 1)); m1 = fmaxf(m1, __shfl_xor_sync(0xffffffffu, m1, 1));
      m0 = fmaxf(m0, __shfl_xor_sync(0xffffffffu, m0, 2)); m1 = fmaxf(m1, __shfl_xor_sync(0xffffffffu, m1, 2));
      a0 = ex2_fast(a0 - m0); a1 = ex2_fast(a1 - m0); b0 = ex2_fast(b0 - m1); b1 = ex2_fast(b1 - m1);
      float s0 = a0 + a1, s1 = b0 + b1;
      s0 += __shfl_xor_sync(0xffffffffu, s0, 1); s1 += __shfl_xor_sync(0xffffffffu, s1, 1);
      s0 += __shfl_xor_sync(0xffffffffu, s0, 2); s1 += __shfl_xor_sync(0xffffffffu, s1, 2);
      s0 = rcp_fast(s0); s1 = rcp_fast(s1);
      pl[b][u] = pack2(a0 * rk[b][0] * s0, a1 * rk[b][1] * s0); ph[b][u] = pack2(b0 * rk[b][2] * s1, b1 * rk[b][3] * s1);
    }
  float O[2][2][4][4];
#pragma unroll
  for (int b = 1; b >= 0; b--)
#pragma unroll
    for (int u = 0; u < 2; u++)
#pragma unroll
      for (int nt = 0; nt < 4; nt++) {
        O[b][u][nt][0] = O[b][u][nt][1] = O[b][u][nt][2] = O[b][u][nt][3] = 0.f;
        mma1688(O[b][u][nt], pl[b][u] & ~mold, ph[b][u] & mold, V[b][u * 4 + nt][0]);
      }
#pragma unroll
  for (int b = 1; b >= 0; b--)
#pragma unroll
    for (int u = 0; u < 2; u++)
#pragma unroll
      for (int nt = 0; nt < 4; nt++) mma1688(O[b][u][nt], 0u, ph[b][u] & ~mold, V[b][u * 4 + nt][1]);
#pragma unroll
  for (int b = 1; b >= 0; b--)
#pragma unroll
    for (int u = 0; u < 2; u++)
#pragma unroll
      for (int nt = 0; nt < 4; nt++) mma1688(O[b][u][nt], pl[b][u] & mold, 0u, HV[b][u * 4 + nt]);
  {
    uint32_t dep = 0;
#pragma unroll
    for (int i = 0; i < 16; i++) dep |= __float_as_uint(O[i >> 3][(i >> 2) & 1][i & 3][0]);
    bar_arrive(3 + wg + (dep & lds32(sbase + OFF_K01 + 4)), 256);
  }
  TRE(wg, l * 32 + 5);
  bf16* op = g_o + (size_t)(T * 128 + (hf * 16 + g) * 2 + (wq >> 1)) * D_DIM + tn * 64 + t * 8;
#pragma unroll
  for (int b = 1; b >= 0; b--)
#pragma unroll
    for (int u = 0; u < 2; u++)
#pragma unroll
      for (int h = 0; h < 2; h++)
        stg128(op + (b * 64 + h * 16) * D_DIM + u * 32, pack2(O[b][u][0][h * 2], O[b][u][0][h * 2 + 1]), pack2(O[b][u][1][h * 2], O[b][u][1][h * 2 + 1]),
               pack2(O[b][u][2][h * 2], O[b][u][2][h * 2 + 1]), pack2(O[b][u][3][h * 2], O[b][u][3][h * 2 + 1]));
  __syncwarp();
  e_arrive(sbase + OFF_OST + wg * 8);
  TRE(wg, l * 32 + 6);
}

__device__ __forceinline__ uint4 ext_row(float mean) {
  const uint32_t hi = pack2(mean, mean);
  return make_uint4(hi, pack2(mean - bf_lo(hi), 0.f), 0, 0);
}
__device__ __forceinline__ uint4 ext_col(float cs) {
  cs *= -0.5f;
  const float hi = bf_lo(pack2(cs, 0.f));
  return make_uint4(pack2(hi, cs - hi), pack2(hi, 0.f), 0, 0);
}

__device__ __forceinline__ void init_down(float (&acc)[1][64], const uint32_t (&xr)[32], uint32_t sbase) {
  const int tid = opaque_tid();
  uint16_t bb0, bb1;
  const uint32_t ba = sbase + OFF_B2 + ((tid >> 5) * 16 + ((tid & 31) >> 2)) * 2;
  asm volatile("ld.shared.u16 %0, [%1];" : "=h"(bb0) : "r"(ba) : "memory");
  asm volatile("ld.shared.u16 %0, [%1];" : "=h"(bb1) : "r"(ba + 16) : "memory");
  const float k = 2.f * GELU_C, bias0 = __uint_as_float((uint32_t)bb0 << 16) * k, bias1 = __uint_as_float((uint32_t)bb1 << 16) * k;
#pragma unroll
  for (int j = 0; j < 16; j++) {
    acc[0][j * 4 + 0] = fmaf(bf_lo(xr[j * 2]), k, bias0); acc[0][j * 4 + 1] = fmaf(bf_hi(xr[j * 2]), k, bias0);
    acc[0][j * 4 + 2] = fmaf(bf_lo(xr[j * 2 + 1]), k, bias1); acc[0][j * 4 + 3] = fmaf(bf_hi(xr[j * 2 + 1]), k, bias1);
  }
}
template <int W>
__device__ __forceinline__ void mixer_up(const Params& P, uint32_t sbase, Cons& c, int l, float (&acc4)[1][64], const uint32_t (&xr)[32]) {
  constexpr int MW = 2 - W, BN = W ? 192 : 128;
  float acc[MW][BN / 2];
  {
    const uint32_t ba = sbase + OFF_B1 + W * 256 + (opaque_tid() & 3) * 4;
#pragma unroll
    for (int j = 0; j < BN / 8; j++) {
      const uint32_t bv = lds32(ba + j * 16);
      const float b0 = bf_lo(bv) * GELU_C, b1 = bf_hi(bv) * GELU_C;
#pragma unroll
      for (int b = 0; b < MW; b++) { acc[b][j * 4 + 0] = acc[b][j * 4 + 2] = b0; acc[b][j * 4 + 1] = acc[b][j * 4 + 3] = b1; }
    }
  }
  gemm_runs<MW, BN, 1, 1, 4, 4, 0, MW * 8192, 0, 0, 1>(P, sbase, c, acc, W);
  TRE(W, l * 32 + 16);
  if (W) init_down(acc4, xr, sbase);
  const int cta = opaque_cta(), tid = opaque_tid(), lane = tid & 31;
  bf16* up = g_u + (size_t)((cta & 7) * 128 + (W ? (cta & 8) * 8 : 0) + ((tid >> 5) & 3) * 16 + (lane >> 2)) * F_DIM +
             (W ? 2048 + (cta >> 4) * 192 : (cta >> 3) * 128) + (lane & 3) * 8;
  float k01 = GELU_B, knext = GELU_B;
  const uint32_t r = P.run[W][c.ri];
  uint32_t so = ((r >> 6) & 31) * 512, e8 = (r >> 8) & 0x38;
  const uint64_t da0 = make_desc(sbase + 16384 + 8192, 8192, 1024), db0 = make_desc(sbase, 16, 1024);
  if (W) { TRC(W, c.ri, 0); }
#pragma unroll
  for (int j = 0; j < 8 - W * 2; j++) {
    if (j == 4 && !W) {
      __syncwarp();
      e_arrive(sbase + OFF_TU0);
    }
    if (W) {
      mbar_wait(sbase + OFF_FULL + 128 + (c.nshr & 7) * 8, (c.nshr >> 3) & 1);
      if (j == 0) { TRC(W, c.ri, 2); }
      c.nshr++;
      wgmma_fence();
#pragma unroll
      for (int k = 0; k < 4; k++) WG<128, 1, 0>::mma(acc4[0], da0 + so + k * 128, db0 + so + k * 2);
      wgmma_commit();
      so = so > (RING_LIM((r >> 25) & 3) - 8) * 512 ? 0 : so + 4 * 512;
      if (j) {
        wgmma_wait<1>();
        if ((tid & 127) == 0) mbar_arrive(sbase + OFF_EMPTY + e8);
        e8 = (e8 + 8) & 0x38;
      }
    }
    if (W || j == 4) k01 = __uint_as_float(lds32(sbase + OFF_K01));
    else k01 = knext;
    if (!W) knext = __uint_as_float(lds32(sbase + OFF_K01));
    const int gr = W ? j : j >> 1, mb = W ? 0 : j & 1;
#pragma unroll
    for (int h = 0; h < 2; h++) {
      const float* v = &acc[mb][gr * 16 + h * 2];
      stg128(up + (mb * 64 + h * 8) * F_DIM + gr * 32, pack2(gelu_tanh(v[0], k01), gelu_tanh(v[1], k01)), pack2(gelu_tanh(v[4], k01), gelu_tanh(v[5], k01)),
             pack2(gelu_tanh(v[8], k01), gelu_tanh(v[9], k01)), pack2(gelu_tanh(v[12], k01), gelu_tanh(v[13], k01)));
    }
  }
  __syncwarp();
  e_arrive(sbase + OFF_TU1 + W * 8);
  TRE(W, l * 32 + 17);
  if (W) {
    wgmma_wait<0>();
    if ((tid & 127) == 0) mbar_arrive(sbase + OFF_EMPTY + e8);
#pragma unroll
    for (int i = 0; i < 64; i++) asm volatile("" : "+f"(acc4[0][i])::"memory");
    TRC(W, c.ri, 3);
    c.ri++;
  } else init_down(acc4, xr, sbase);
}

__device__ __forceinline__ void row_stats(const uint4 (&raw)[8], int row0, unsigned tag, int lane) {
  float s[2], q[2];
#pragma unroll
  for (int rr = 0; rr < 2; rr++) {
    s[rr] = 0.f; q[rr] = 0.f;
#pragma unroll
    for (int i = 0; i < 4; i++) {
      float v[8];
      unpack8(raw[rr * 4 + i], v);
      s[rr] += ((v[0] + v[1]) + (v[2] + v[3])) + ((v[4] + v[5]) + (v[6] + v[7]));
#pragma unroll
      for (int e = 0; e < 8; e++) q[rr] = fmaf(v[e], v[e], q[rr]);
    }
  }
#pragma unroll
  for (int o = 16; o > 0; o >>= 1)
#pragma unroll
    for (int rr = 0; rr < 2; rr++) { s[rr] += __shfl_xor_sync(0xffffffffu, s[rr], o); q[rr] += __shfl_xor_sync(0xffffffffu, q[rr], o); }
  const int row = row0 + (lane & 1);
  if (lane < 16)
    __stcg(&g_statsA[((row >> 6) * 8 + (lane >> 1)) * 64 + (row & 63)],
           make_uint4(__float_as_uint(((lane & 1) ? s[1] : s[0]) * 0.125f), tag, __float_as_uint(((lane & 1) ? q[1] : q[0]) * 0.125f), tag));
}
__device__ __forceinline__ uint4 ldg_v(const uint4* p) {
  uint4 v;
  asm volatile("ld.global.nc.v4.u32 {%0,%1,%2,%3}, [%4];" : "=r"(v.x), "=r"(v.y), "=r"(v.z), "=r"(v.w) : "l"(p) : "memory");
  return v;
}
__device__ __noinline__ void startup(const bf16* __restrict__ x, const bf16* __restrict__ wqkv, const bf16* __restrict__ b1,
                                     const bf16* __restrict__ b2, uint32_t sbase, unsigned tag, unsigned delay) {
  const int cta = LCTA, lane = threadIdx.x & 31, wq = __shfl_sync(0xffffffffu, (threadIdx.x >> 5) & 3, 0), m = cta >> 3, j = cta & 7;
  const int i = threadIdx.x & 127, row0 = cta * 8 + wq * 2;
  __nanosleep(delay);
  const uint4* xs = reinterpret_cast<const uint4*>(x + (size_t)row0 * D_DIM) + lane;
  const uint4* ws = reinterpret_cast<const uint4*>(wqkv + (size_t)(j * 128 + wq * 32 + (lane >> 3)) * (3 * D_DIM) + m * 64) + (lane & 7);
  uint4 raw[8], wr[8];
#pragma unroll
  for (int k = 0; k < 8; k++) raw[k] = ldg_v(xs + k * 32);
#pragma unroll
  for (int k = 0; k < 8; k++) wr[k] = ldg_v(ws + k * 4 * 384);
  if (wq < 3) __stcg(&g_cs[j * 1536 + m * 96 + i], make_uint4(0, 0, 0, 0));
  if (i < 40) sts128(sbase + OFF_B1 + i * 16, *reinterpret_cast<const uint4*>(b1 + (i < 16 ? m * 128 : 1920 + (m >> 1) * 192) + i * 8));
  if (i >= 64 && i < 80) sts128(sbase + OFF_B2 + (i - 64) * 16, *reinterpret_cast<const uint4*>(b2 + (((i >> 3) & 1) * 16 + m) * 64 + (i & 7) * 8));
  const uint32_t sa = sbase + OFF_HALO;
#define WAITFOR(v) if (v[7].x == tag + v[7].y * 65536 + 12345 && v[6].w == 99) delay++
#define COLSUM(v, p)                                                                                                          \
  {                                                                                                                           \
    float s[8];                                                                                                               \
    _Pragma("unroll") for (int e = 0; e < 8; e++) s[e] = 0.f;                                                                 \
    _Pragma("unroll") for (int k = 0; k < 8; k++) {                                                                           \
      float f[8];                                                                                                             \
      unpack8(v[k], f);                                                                                                       \
      _Pragma("unroll") for (int e = 0; e < 8; e++) s[e] += f[e];                                                             \
    }                                                                                                                         \
    const uint32_t a = sa + (wq * 4 + (lane >> 3)) * 768 + (p) * 256 + (lane & 7) * 32;                                       \
    sts128(a, make_uint4(__float_as_uint(s[0]), __float_as_uint(s[1]), __float_as_uint(s[2]), __float_as_uint(s[3])));       \
    sts128(a + 16, make_uint4(__float_as_uint(s[4]), __float_as_uint(s[5]), __float_as_uint(s[6]), __float_as_uint(s[7])));  \
  }
  uint4 w2[8];
  WAITFOR(raw);
#pragma unroll
  for (int k = 0; k < 8; k++) w2[k] = ldg_v(ws + 128 + k * 4 * 384 + (delay >> 31));
  row_stats(raw, row0, tag, lane);
  WAITFOR(wr);
#pragma unroll
  for (int k = 0; k < 8; k++) raw[k] = ldg_v(ws + 256 + k * 4 * 384 + (delay >> 31));
#pragma unroll 1
  for (int p = 0; p < 3; p++) {
    COLSUM(wr, p);
#pragma unroll
    for (int k = 0; k < 8; k++) { wr[k] = w2[k]; w2[k] = raw[k]; }
  }
  bar_sync(8, 128);
  if (wq < 3) {
    float a = 0.f, b = 0.f;
#pragma unroll
    for (int r = 0; r < 16; r++) { const float2 v = lds64f(sa + r * 768 + i * 8); a += v.x; b += v.y; }
    __stcg(&g_cs[j * 1536 + m * 96 + i], make_uint4(__float_as_uint(a), tag, __float_as_uint(b), tag));
  }
  TRE(1, 24);
#pragma unroll
  for (int k = 0; k < 8; k++) raw[k] = ldg_v(xs + 1024 * 128 + k * 32);
#pragma unroll 1
  for (int q = wq == 3 ? 0 : 1; q < 2; q++) {
    const int tk = q ? i : lane - 32;
    const int row = max(j * 128 + tk, 0);
    const uint4* p = &g_statsA[(row >> 6) * 512 + (row & 63)];
    uint4 v;
    for (int it = 0; it < (1 << 20); it++) {
      v = ld_volatile4(p);
      if (__all_sync(0xffffffffu, v.y == tag && v.w == tag)) break;
      __nanosleep(200);
    }
    const float mean = __uint_as_float(v.x) * (8.0f / D_DIM);
    const float rs = rsqrtf(fmaxf(fmaf(__uint_as_float(v.z), 8.0f / D_DIM, -mean * mean), 0.f) + 1e-5f);
    if (tk >= -16) sts32(sbase + OFF_ST + ((tk & 1) * 72 + 8 + (tk >> 1)) * 4, __float_as_uint(rs));
    if (q) sts128(sbase + OFF_EXT + ((i & 64) + (i & 1) * 32 + ((i & 63) >> 1)) * 16, ext_row(mean));
  }
  if (wq < 3) {
    const uint4* p = &g_cs[m * 96 + i];
    uint4 v[8];
    for (int it = 0; it < (1 << 20); it++) {
      bool ok = true;
#pragma unroll
      for (int r = 0; r < 8; r++) v[r] = ld_volatile4(p + r * 1536);
#pragma unroll
      for (int r = 0; r < 8; r++) ok = ok && v[r].y == tag && v[r].w == tag;
      if (__all_sync(0xffffffffu, ok)) break;
      __nanosleep(100);
    }
    float a = 0.f, b = 0.f;
#pragma unroll
    for (int r = 0; r < 8; r++) { a += __uint_as_float(v[r].x); b += __uint_as_float(v[r].z); }
    sts64f(sbase + OFF_CS + i * 8, a, b);
    sts128(sbase + OFF_EXT + 2048 + i * 32, ext_col(a));
    sts128(sbase + OFF_EXT + 2048 + i * 32 + 16, ext_col(b));
  }
  fence_proxy_async_smem();
  bar_sync(8, 128);
  if (i == 0) mbar_arrive(sbase + OFF_STR);
  TRE(1, 27);
  row_stats(raw, row0 + 1024, tag, lane);
  __syncwarp();
}

__device__ __forceinline__ void poll8(uint4 (&v)[8], const uint4* p, int stride, unsigned tag) {
#pragma unroll 1
  for (int it = 0; it < (1 << 20); it++) {
    bool ok = true;
#pragma unroll
    for (int i = 0; i < 8; i++) v[i] = ld_volatile4(p + i * stride);
#pragma unroll
    for (int i = 0; i < 8; i++) ok = ok && v[i].y == tag && v[i].w == tag;
    if (SKEL || __all_sync(0xffffffffu, ok)) break;
    __nanosleep(200);
  }
}

__global__ void __launch_bounds__(384, 1)
mega_kernel(const __grid_constant__ Params P, const bf16* __restrict__ x, const bf16* __restrict__ wqkv, const bf16* __restrict__ b1,
            const bf16* __restrict__ b2, bf16* __restrict__ out) {
  extern __shared__ __align__(1024) uint8_t smem_raw[];
  const uint32_t sbase = smem_u32(smem_raw);
  if (threadIdx.x == 0) sts128(sbase + OFF_K01, make_uint4(__float_as_uint(GELU_B), 0, logical_cta(P.map), 0x3f800000));
  if (threadIdx.x == 256) {
    for (int s = 0; s < 32; s++) mbar_init(sbase + OFF_FULL + s * 8, 2);
    for (int w = 0; w < 2; w++) {
      mbar_init(sbase + OFF_STR + w * 8, 1);
      mbar_init(sbase + OFF_OST + w * 8, 4); mbar_init(sbase + OFF_TR + w * 8, 4);
      mbar_init(sbase + OFF_TU0 + w * 8, 4); mbar_init(sbase + OFF_TU1 + w * 8, 4);
    }
    for (int s = 0; s < 10; s++) mbar_init(sbase + OFF_DEP + s * 8, 1);
    asm volatile("fence.mbarrier_init.release.cluster;" ::: "memory");
  }
  __syncthreads();

  if (LCTA < 0) {
    if (threadIdx.x == 0) {
      const unsigned epoch = *(volatile unsigned*)&g_epoch;
#pragma unroll 1
      for (int it = 0; it < (1 << 20) && (int)(*(volatile unsigned*)&g_sync[2] - (epoch * 9 + 1) * NCTA) < 0; it++) __nanosleep(2000);
    }
    return;
  }
  const int warp = __shfl_sync(0xffffffffu, threadIdx.x >> 5, 0);
  const int wg = warp >> 2;
  if (__shfl_sync(0xffffffffu, threadIdx.x >> 8, 0) == 0) {
    asm volatile("setmaxnreg.inc.sync.aligned.u32 %0;" ::"n"(RHI));
    TRE(wg, 63);
    TRG(wg, 63);
    const unsigned epoch = *(volatile unsigned*)&g_epoch;
    if (wg == 1) startup(x, wqkv, b1, b2, sbase, epoch * 2 + 1, P.sud);
    Cons c;
    c.nsolo = 0; c.nshr = 0; c.ri = 0;
    float acc4[1][64];
#pragma unroll
    for (int i = 0; i < 64; i++) acc4[0][i] = 0.f;
#pragma unroll 1
    for (int l = -1;; l++) {
      if (l >= 0) {
        uint32_t pk[32];
        gemm_runs<1, 128, 1, 0, 3, 4, 16384, 0, 8192, 0, DP4>(P, sbase, c, acc4, wg);
        TRE(wg, l * 32 + 20);
#pragma unroll
        for (int i = 0; i < 64; i++) acc4[0][i] *= 0.5f / GELU_C;
        const int cta = opaque_cta(), tid = opaque_tid(), lane = tid & 31, rw = ((tid >> 5) & 3) * 16;
#pragma unroll
        for (int j = 0; j < 16; j++) {
          pk[j * 2] = pack2(acc4[0][j * 4 + 0], acc4[0][j * 4 + 1]);
          pk[j * 2 + 1] = pack2(acc4[0][j * 4 + 2], acc4[0][j * 4 + 3]);
        }
        store_tile128(pk, (l ? out : g_x2) + (size_t)((wg * 16 + (cta >> 3)) * 64 + rw + (lane >> 2)) * D_DIM + (cta & 7) * 128 + (lane & 3) * 8,
                      sbase + OFF_TR + wg * 8, lane);
        TRE(wg, l * 32 + 21);
        if (l == 0) tile_stats(acc4[0], &g_statsA[(wg * 16 + (cta >> 3)) * 512 + (cta & 7) * 64 + rw + (lane >> 2)], epoch * 2 + 2, lane & 3,
                               __uint_as_float(lds32(sbase + OFF_K01 + 4)));
        TRE(wg, l * 32 + 22);
        if (l) break;
      }
      l++;
      {
        float acc[2][96];
#pragma unroll
        for (int b = 0; b < 2; b++)
#pragma unroll
          for (int i = 0; i < 96; i++) acc[b][i] = 0.f;
        gemm_runs<2, 192, 0, 1, 5, 5, 0, 16384, 0, 0, 1>(P, sbase, c, acc, wg);
        attention(P, acc, sbase, c, wg, l, epoch * 2 + l + 1);
      }
      uint32_t xr[32];
      {
        float acc[1][64];
        {
          if (PREW) {
            const int cta = opaque_cta(), tid = opaque_tid();
            if ((tid & 3) < 2) __stcg(&g_statsB[(wg * 16 + (cta >> 3)) * 512 + (cta & 7) * 64 + ((tid >> 5) & 3) * 16 + ((tid & 31) >> 2) + (tid & 3) * 8], make_uint4(0, 0, 0, 0));
          }
          const int cta = opaque_cta(), tid = opaque_tid();
          const uint4* rp = reinterpret_cast<const uint4*>((l ? g_x2 : x) + (size_t)((wg * 16 + (cta >> 3)) * 64 + ((tid >> 5) & 3) * 16 + ((tid & 31) >> 2)) * D_DIM +
                                                           (cta & 7) * 128) + (tid & 3);
          __nanosleep(P.rsd);
          uint4 q[8];
#pragma unroll
          for (int i = 0; i < 8; i++) q[i] = __ldcg(rp + (i & 1) * D_DIM + (i >> 1) * 4);
#pragma unroll
          for (int i = 0; i < 8; i++) {
            quad_transpose(q[i].x, q[i].y, q[i].z, q[i].w, tid & 3);
            float* a = &acc[0][(i >> 1) * 16 + (i & 1) * 2];
            a[0] = bf_lo(q[i].x); a[1] = bf_hi(q[i].x); a[4] = bf_lo(q[i].y); a[5] = bf_hi(q[i].y);
            a[8] = bf_lo(q[i].z); a[9] = bf_hi(q[i].z); a[12] = bf_lo(q[i].w); a[13] = bf_hi(q[i].w);
          }
        }
        gemm_runs<1, 128, 0, 1, 3, 3, 16384, 0, 0, 0, DP2>(P, sbase, c, acc, wg);
        TRE(wg, l * 32 + 10);
        const int cta = opaque_cta(), tid = opaque_tid(), lane = tid & 31, rw = ((tid >> 5) & 3) * 16;
        const unsigned tag = epoch * 2 + l + 1;
        uint4* sb = &g_statsB[(wg * 16 + (cta >> 3)) * 512 + rw];
        tile_stats(acc[0], sb + (cta & 7) * 64 + (lane >> 2), tag, lane & 3);
        TRE(wg, l * 32 + 11);
#pragma unroll
        for (int j = 0; j < 16; j++) {
          xr[j * 2] = pack2(acc[0][j * 4 + 0], acc[0][j * 4 + 1]);
          xr[j * 2 + 1] = pack2(acc[0][j * 4 + 2], acc[0][j * 4 + 3]);
        }
#pragma unroll
        for (int i = 0; i < 8; i++) {
          const int o = (i >> 1) * 8 + (i & 1);
          quad_transpose(xr[o], xr[o + 2], xr[o + 4], xr[o + 6], lane & 3);
        }
        const uint4* sp = sb + (lane & 1) * 256 + (lane >> 1);
        uint4 a, b, cc, d;
        int it = 0;
        __nanosleep(P.pre);
        while (true) {
          a = ld_volatile4(sp); b = ld_volatile4(sp + 64); cc = ld_volatile4(sp + 128); d = ld_volatile4(sp + 192);
          bool ok = a.y == tag && a.w == tag && b.y == tag && b.w == tag && cc.y == tag && cc.w == tag && d.y == tag && d.w == tag;
          if (SKEL || ok || ++it > (1 << 20)) break;
          __nanosleep(P.poll);
        }
        __syncwarp();
        TRE(wg, l * 32 + 12);
        float mean = (__uint_as_float(a.x) + __uint_as_float(b.x)) + (__uint_as_float(cc.x) + __uint_as_float(d.x));
        float v = (__uint_as_float(a.z) + __uint_as_float(b.z)) + (__uint_as_float(cc.z) + __uint_as_float(d.z));
        mean += __shfl_xor_sync(0xffffffffu, mean, 1);
        v += __shfl_xor_sync(0xffffffffu, v, 1);
        mean *= (1.0f / D_DIM);
        v = fmaxf(fmaf(v, 1.0f / D_DIM, -mean * mean), 0.f);
        const float rs = GELU_C * rsqrtf(fmaf(v + 1e-5f, 1e-5f, v));
        mean *= -rs;
        const int g2 = (lane >> 2) * 2;
        const float nm0 = __shfl_sync(0xffffffffu, mean, g2), rs0 = __shfl_sync(0xffffffffu, rs, g2);
        const float nm1 = __shfl_sync(0xffffffffu, mean, g2 + 16), rs1 = __shfl_sync(0xffffffffu, rs, g2 + 16);
        uint32_t hk[32];
#pragma unroll
        for (int j = 0; j < 16; j++) {
          hk[j * 2] = pack2(fmaf(acc[0][j * 4 + 0], rs0, nm0), fmaf(acc[0][j * 4 + 1], rs0, nm0));
          hk[j * 2 + 1] = pack2(fmaf(acc[0][j * 4 + 2], rs1, nm1), fmaf(acc[0][j * 4 + 3], rs1, nm1));
        }
        store_tile128(hk, g_h + (size_t)((wg * 16 + (cta >> 3)) * 64 + rw + (lane >> 2)) * D_DIM + (cta & 7) * 128 + (lane & 3) * 8, sbase + OFF_TR + wg * 8, lane);
        TRE(wg, l * 32 + 13);
      }
      if (wg == 1) mixer_up<1>(P, sbase, c, l, acc4, xr);
      else mixer_up<0>(P, sbase, c, l, acc4, xr);
      l--;
    }
    TRE(wg, 62);
    TRG(wg, 62);
    if ((threadIdx.x & 127) == 0) {
      const unsigned v = atomicAdd(&g_exit, 1);
      if (v == (epoch + 1) * 2 * NCTA - 1) { __threadfence(); *(volatile unsigned*)&g_epoch = epoch + 1; }
    }
  } else {
    asm volatile("setmaxnreg.dec.sync.aligned.u32 %0;" ::"n"(RLO));
    if (warp < 10) {
      if (warp == 8) producer<0>(P, sbase);
      else producer<1>(P, sbase);
    } else {
      const unsigned epoch = __shfl_sync(0xffffffffu, *(volatile unsigned*)&g_epoch, 0);
      const int cta = LCTA, w = warp - 10, j = cta & 7;
      sts32(sbase + OFF_SFR, epoch);
      unsigned* const cn = &g_sync[2 + w];
      unsigned tgt = epoch * (9 - 2 * w) * NCTA;
      if (w == 1 && (threadIdx.x & 31) < 11) prefetch_tmap(reinterpret_cast<const CUtensorMap*>(&P) + (threadIdx.x & 31));
      __syncwarp();
#pragma unroll 1
      for (int q9 = 0; q9 < 9; q9++) {
        const int l = q9 >= 5, q = q9 - l * 5;
        if (q == 0 && (w | l)) {
          const int lane = opaque_tid() & 31;
          const uint32_t half = sbase + OFF_EXT + (opaque_tid() & 32) * 160;
          mbar_wait(sbase + OFF_OST + 8 - w * 8, w ? l : 0);
#pragma unroll 1
          for (int r = 0; r < 6; r++) sts128(half + 2048 + (r * 32 + lane) * 16, ext_col(__uint_as_float(lds32(sbase + OFF_CS + (r * 32 + lane) * 4))));
#pragma unroll 1
          for (int t0 = -32; t0 < 128; t0 += 32) {
            float mean = 0.f, var = 0.f;
            {
              const int row = max((w * 8 + j) * 128 + t0 + lane, 0);
              uint4 v[8];
              poll8(v, &g_statsA[(row >> 6) * 512 + (row & 63)], 64, epoch * 2 + l + 1);
#pragma unroll
              for (int i = 0; i < 8; i++) { mean += __uint_as_float(v[i].x); var += __uint_as_float(v[i].z); }
            }
            const int tk = t0 + (opaque_tid() & 31);
            mean *= (1.0f / D_DIM);
            const float rs = rsqrtf(fmaxf(fmaf(var, 1.0f / D_DIM, -mean * mean), 0.f) + 1e-5f);
            if (tk >= -16) sts32(sbase + OFF_ST + ((tk & 1) * 72 + 8 + (tk >> 1)) * 4, __float_as_uint(rs));
            if (t0 >= 0) sts128(half + ((tk & 64) + (tk & 1) * 32 + ((tk & 63) >> 1)) * 16, ext_row(mean));
          }
          fence_proxy_async_smem();
          __syncwarp();
          e_arrive(sbase + OFF_STR + w * 8);
          TRA(w, l * 32 + 8);
        }
        if (w && q == 2) continue;
        mbar_wait(sbase + OFF_OST + (q == 4 ? 1 : q) * 16 + w * 8, q == 1 ? 0 : q == 4 ? 1 : l);
        TRA(w, l * 32 + ((0x1c001a0e07ull >> (q * 8)) & 31));
        e_red_release(cn);
        TRA(w, l * 32 + ((0x1713120f09ull >> (q * 8)) & 31));
        spin_until(cn, tgt += NCTA);
        e_arrive(sbase + OFF_DEP + (((0x86531 >> (q * 4)) & 15) + w) * 8);
      }
    }
  }
}

typedef CUresult (*PFN_encodeTiled)(CUtensorMap*, CUtensorMapDataType, cuuint32_t, void*, const cuuint64_t*,
                                    const cuuint64_t*, const cuuint32_t*, const cuuint32_t*, CUtensorMapInterleave,
                                    CUtensorMapSwizzle, CUtensorMapL2promotion, CUtensorMapFloatOOBfill);
static PFN_encodeTiled g_encode = nullptr;

static CUtensorMap make_map5(const void* ptr, int d0, int d1, int d2, int d3, int d4, int s1, int s2, int s3, int s4, int b1, int b2, int b3, int b4) {
  CUtensorMap m;
  cuuint64_t dims[5] = {(cuuint64_t)d0, (cuuint64_t)d1, (cuuint64_t)d2, (cuuint64_t)d3, (cuuint64_t)d4};
  cuuint64_t strides[4] = {(cuuint64_t)s1 * 2, (cuuint64_t)s2 * 2, (cuuint64_t)s3 * 2, (cuuint64_t)s4 * 2};
  cuuint32_t box[5] = {64, (cuuint32_t)b1, (cuuint32_t)b2, (cuuint32_t)b3, (cuuint32_t)b4};
  cuuint32_t es[5] = {1, 1, 1, 1, 1};
  g_encode(&m, CU_TENSOR_MAP_DATA_TYPE_BFLOAT16, 5, (void*)ptr, dims, strides, box, es, CU_TENSOR_MAP_INTERLEAVE_NONE,
           CU_TENSOR_MAP_SWIZZLE_128B, CU_TENSOR_MAP_L2_PROMOTION_L2_128B, CU_TENSOR_MAP_FLOAT_OOB_FILL_NONE);
  return m;
}
static CUtensorMap make_map(const void* ptr, int rows, int cols, int box_rows, int nblk = 1, int bstep = 64) {
  return make_map5(ptr, cols - (nblk - 1) * bstep, rows, nblk, 1, 1, cols, bstep, 64, 64, box_rows, nblk, 1, 1);
}
static CUtensorMap make_map_perm(const void* ptr, int rows, int cols) {
  return make_map5(ptr, cols, 2, 4, 4, rows / 32, cols, 8 * cols, 2 * cols, 32 * cols, 2, 4, 4, 2);
}

#define tune(n, d) (d)
#define PX tune("PX", 7)
#define PA1 tune("PA1", 2)
#define PY tune("PY", 7)
#define PB1 tune("PB1", 0)
#define PZ tune("PZ", 16)
#define PV tune("PV", 16)
#define PA4 tune("PA4", 12)

struct Sched {
  Params& P;
  int pos = 0, e = 0, nr[2] = {0, 0}, l = 0;
  int cap[12] = {8, 8, 8, 8, tune("C2", 8), tune("C2", 8), 8, tune("C3", 8), 8, tune("C4", 8), tune("C4", 8), 8};
  int lastk[2] = {-1, -1}, laste[2] = {0, 0};
  int tail = 0, cnt[3] = {0, 0, 0}, owner[RING_U], big = 0, lastlc = -1;
  Sched(Params& p) : P(p) { P.nseg = 0; P.npace = 0; for (int u = 0; u < RING_U; u++) owner[u] = -1; }
  int pending = 0;
  void pace(int on) { pending = on != 0; P.npace += pending; }
  void add(int kind, int k0, int n, int dep, int pre, int post, int fl, int ks = 1, int x = 0) {
    if (n <= 0) return;
    static const int size[12] = {5, 5, 3, 3, 3, 3, 4, 4, 6, 3, 3, 4};
    const int sz = size[kind], sh = kind == K_G4S, w = (kind < K_G3S ? kind : kind - 1) & 1, set = sh ? 2 : w;
    const int lc = kind < K_G2 ? 1 : big * 2, lim = RING_LIM(lc), pad = lc != lastlc;
    lastlc = lc;
    if (tune("ALN", 1)) pos = (pos + sz - 1) / sz * sz;
    if (pos + sz > lim) pos = 0;
    for (int v = 0; v < 2; v++)
      if (sh || v == w) {
        const int last = ((fl >> (2 + v)) & 1) | (fl >> 4), drain = ((fl >> v) & 1) | ((fl >> (2 + v)) & 1);
        const int pr = sh && !v ? 0 : pre, po = sh && v ? 0 : post;
        if (nr[v] && lastk[v] == kind && laste[v] == e && !pad && !pr && !(x & (v ? 19 : 3)) && !(P.run[v][nr[v] - 1] & 0x11f80000u) && !tune("NOMERGE", 0)) {
          P.run[v][nr[v] - 1] += n | po << 19 | drain << 23 | last << 24;
          laste[v] = e + n;
          continue;
        }
        lastk[v] = kind; laste[v] = e + n;
        P.run[v][nr[v]++] = n | pos << 6 | (e & 7) << 11 | sh << 14 | (sh && !v ? 0 : pre) << 15 | (sh && v ? 0 : post) << 19 | drain << 23 | last << 24 |
                            lc << 25 | (v ? x >> 4 : 0) << 28;
      }
    int i0 = 0;
    const uint32_t px = P.nseg ? P.seg[P.nseg - 1].x : ~0u;
    const uint32_t xf = pending;
    pending = 0;
    if (!xf && !pad && P.nseg && (int)(px & 15) == kind && !dep && (int)((px >> 16) & 1) == ks - 1 && (int)(((px >> 4) & 63) + ((px >> 10) & 63) * ks) == k0) {
      i0 = (px >> 10) & 63;
      P.seg[P.nseg - 1].x += n << 10;
    } else P.seg[P.nseg++] = make_uint2(kind | k0 << 4 | n << 10 | (ks - 1) << 16 | dep << 17 | pos << 22 | l << 27 | xf << 28 | lc << 29, (cnt[set] & 7) << 29);
    for (int i = i0; i < i0 + n; i++) {
      int need = e - cap[kind];
      for (int u = pos; u < pos + sz; u++) { if (owner[u] > need) need = owner[u]; owner[u] = e; }
      int nw = need + 1 > tail ? need + 1 - tail : 0;
      if (i >= 14 && nw == 0) nw = 1;
      if (nw > 3 || (i >= 14 && nw != 1)) P.nseg = -1000000;
      if (i < 14) P.seg[P.nseg - 1].y |= nw << (2 * i);
      tail += nw;
      e++;
      pos += sz;
      if (i + 1 < i0 + n && pos + sz > lim) pos = 0;
    }
    cnt[set] += n;
  }
};

static void build_schedule(Params& P) {
  Sched s(P);
  P.map = tune("MAP", 0);
  P.u1d = tune("U1D", 0);
  P.ef[0] = tune("EFW", 0);
  P.ef[1] = tune("EFA", 0);
  P.rsd = tune("RSD", 500);
  P.u0d = tune("U0D", 0);
  P.sud = tune("SUD", 500);
  P.pre = tune("PRE", 150);
  P.poll = tune("POLL", 40);
  const int pm = tune("PM", 0), sk4 = tune("SK4", 6);
  for (int l = 0; l < 2; l++) {
    s.l = l;
    const int b = l * 16, a4 = l ? tune("PA4L", 0) : PA4;
    s.add(K_G1, 0, 8, l ? E_X : 0, 0, 0, 0);
    s.pace(pm & 512);
    s.add(K_G1, 8, 5, 0, 0, 0, 16);
    s.add(K_G1, 13, 3, 0, 0, 1, 0);
    s.pace(pm & 256);
    s.add(K_G1 + 1, 0, PA1, l ? E_X + 1 : 0, 1, 0, 3);
    s.add(K_G1 + 1, PA1, PX - PA1, 0, 3, 0, 3);
    s.pace(pm & 1);
    s.add(K_G2, 0, 16, b + E_O, 0, 1, 12);
    s.add(K_G1 + 1, PX, 13 - PX, 0, 1, 0, 16);
    s.add(K_G1 + 1, 13, 3, 0, 0, PB1 ? 2 : 0, 0);
    s.add(K_G3, 0, PB1, b + E_H, 2, 0, 3);
    s.add(K_G3, PB1, PY - PB1, PB1 ? 0 : b + E_H, 4, 0, 3);
    s.pace(pm & 2);
    s.add(K_G2 + 1, 0, 16, b + E_O + 1, 0, 2, 12);
    s.big = tune("BIG", 1);
    s.add(K_G3, PY, 16 - PY, 0, 2, 0, 3);
    const int pv = PV, pw = tune("PW", 0);
    s.pace(pm & 4);
    s.add(K_G3 + 1, 0, PZ, 0, 0, 0, 3);
    s.pace(pm & 8);
    s.add(K_G3, 16, pv, b + E_H + 1, 0, pv == 16, pv == 16 ? 12 : 3);
    s.add(K_G3 + 1, PZ, pv == 16 ? 0 : pw, 0, 0, 0, 3);
    s.add(K_G3, 16 + pv, 16 - pv, 0, 0, 1, 12);
    s.pace(pm & 16);
    s.add(K_G3 + 1, PZ + (pv == 16 ? 0 : pw), 32 - PZ - (pv == 16 ? 0 : pw), 0, 1, 0, 12);
    const int k4 = l ? tune("SK4L", 5) : sk4;
    s.pace(pm & 32);
    s.add(K_G4S, 0, 6, b + E_UA, 0, 0, 0, 2, 16);
    s.add(K_G4S, 12, 10, 0, 0, 0, 0, 2);
    s.pace(pm & 64);
    s.add(K_G4S, 1, 16, b + E_UB, 0, 0, a4 ? 2 : 0, 2);
    s.pace(pm & 128);
    s.add(K_G4, 32, a4, b + E_U1, 0, 0, 0);
    s.add(K_G4S, 32 + a4, 17 - a4, a4 ? 0 : b + E_U1, 0, 0, 0);
    if (l == 0) s.big = 0;
    s.add(K_G4S, 49, 7 - k4, 0, 0, 0, k4 ? 2 : a4 ? 4 : 12);
    s.add(K_G4S, 56 - k4, k4, 0, 1, 1, a4 ? 4 : 12);
    s.add(K_G4 + 1, 32, a4, 0, 0, 0, 12);
  }
}

extern "C" void kernel_launch(void* const* d_in, const int* in_sizes, int n_in, void* d_out, int out_size) {
  const bf16* x = (const bf16*)d_in[0];
  const bf16* wqkv = (const bf16*)d_in[1];
  const bf16* wo = (const bf16*)d_in[2];
  const bf16* w1 = (const bf16*)d_in[4];
  const bf16* b1 = (const bf16*)d_in[5];
  const bf16* w2 = (const bf16*)d_in[6];
  const bf16* b2 = (const bf16*)d_in[7];
  bf16* out = (bf16*)d_out;

  if (!g_encode) {
    void* fn = nullptr;
    cudaDriverEntryPointQueryResult st;
    cudaGetDriverEntryPoint("cuTensorMapEncodeTiled", &fn, cudaEnableDefault, &st);
    g_encode = (PFN_encodeTiled)fn;
  }
  bf16 *h, *o, *u, *x2;
  cudaGetSymbolAddress((void**)&h, g_h);
  cudaGetSymbolAddress((void**)&o, g_o);
  cudaGetSymbolAddress((void**)&u, g_u);
  cudaGetSymbolAddress((void**)&x2, g_x2);
  Params P;
  P.xq[0] = make_map5(x, D_DIM, 32, 2, 32, 1, 2 * D_DIM, D_DIM, 64 * D_DIM, 64, 32, 2, 2, 1);
  P.xq[1] = make_map5(x2, D_DIM, 32, 2, 32, 1, 2 * D_DIM, D_DIM, 64 * D_DIM, 64, 32, 2, 2, 1);
  P.wqkv = make_map(wqkv, D_DIM, 3 * D_DIM, 64, 3, 1024);
  P.o_k = make_map(o, S_LEN, D_DIM, 64);
  P.wo = make_map_perm(wo, D_DIM, D_DIM);
  P.h_m = make_map(h, S_LEN, D_DIM, 64, 2);
  P.h_1 = make_map(h, S_LEN, D_DIM, 64);
  P.w1a = make_map(w1, S_LEN, F_DIM, 64, 2);
  P.w1b = make_map(w1, S_LEN, F_DIM, 64, 3);
  P.w2 = make_map_perm(w2, F_DIM, S_LEN);
  P.u_k = make_map(u, D_DIM, F_DIM, 128);
  build_schedule(P);
  cudaFuncSetAttribute(mega_kernel, cudaFuncAttributeMaxDynamicSharedMemorySize, SMEM_TOTAL);
  int sms = 0;
  cudaDeviceGetAttribute(&sms, cudaDevAttrMultiProcessorCount, 0);
  mega_kernel<<<sms == 132 && tune("G132", 1) ? 132 : NCTA, 384, SMEM_TOTAL, cudaStreamPerThread>>>(P, x, wqkv, b1, b2, out);
}
```

```cpp
#include <cuda_runtime.h>
#include <cuda_bf16.h>
#include <cuda.h>
#include <stdint.h>

typedef __nv_bfloat16 bf16;

#define S_LEN 2048
#define D_DIM 1024
#define F_DIM 3584
#define NCTA 128

__device__ __forceinline__ uint32_t smem_u32(const void* p) { return (uint32_t)__cvta_generic_to_shared(p); }
__device__ __forceinline__ void mbar_init(uint32_t bar, uint32_t count) {
  asm volatile("mbarrier.init.shared::cta.b64 [%0], %1;" ::"r"(bar), "r"(count) : "memory");
}
__device__ __forceinline__ void mbar_arrive(uint32_t bar) {
  asm volatile("mbarrier.arrive.shared::cta.b64 _, [%0];" ::"r"(bar) : "memory");
}
__device__ __forceinline__ void mbar_arrive_n(uint32_t bar, uint32_t n) {
  asm volatile("mbarrier.arrive.shared::cta.b64 _, [%0], %1;" ::"r"(bar), "r"(n) : "memory");
}
__device__ __forceinline__ void mbar_wait(uint32_t bar, uint32_t parity) {
  asm volatile(
      "{\n.reg .pred p;\n.reg .u32 c;\nmov.u32 c, 0;\n"
      "WAIT_LOOP:\n"
      "mbarrier.try_wait.parity.shared::cta.b64 p, [%0], %1;\n"
      "@p bra.uni WAIT_DONE;\n"
      "add.u32 c, c, 1;\n"
      "setp.lt.u32 p, c, 4194304;\n"
      "@p bra.uni WAIT_LOOP;\n"
      "trap;\n"
      "WAIT_DONE:\n}\n" ::"r"(bar), "r"(parity) : "memory");
}
__device__ __forceinline__ void prefetch_tmap(const CUtensorMap* tm) {
  asm volatile("prefetch.tensormap [%0];" ::"l"((uint64_t)tm) : "memory");
}
__device__ __forceinline__ void wgmma_fence() { asm volatile("wgmma.fence.sync.aligned;" ::: "memory"); }
__device__ __forceinline__ void wgmma_commit() { asm volatile("wgmma.commit_group.sync.aligned;" ::: "memory"); }
template <int N>
__device__ __forceinline__ void wgmma_wait() { asm volatile("wgmma.wait_group.sync.aligned %0;" ::"n"(N) : "memory"); }
__device__ __forceinline__ void bar_sync(int id, int nthreads) { asm volatile("bar.sync %0, %1;" ::"r"(id), "r"(nthreads) : "memory"); }
__device__ __forceinline__ void bar_arrive(int id, int nthreads) { asm volatile("bar.arrive %0, %1;" ::"r"(id), "r"(nthreads) : "memory"); }
__device__ __forceinline__ uint64_t make_desc(uint32_t addr, uint32_t lbo_bytes, uint32_t sbo_bytes) {
  uint64_t d = 0;
  d |= (uint64_t)((addr & 0x3FFFF) >> 4);
  d |= (uint64_t)((lbo_bytes & 0x3FFFF) >> 4) << 16;
  d |= (uint64_t)((sbo_bytes & 0x3FFFF) >> 4) << 32;
  d |= (uint64_t)1 << 62;
  return d;
}
template<int TA, int TB>
__device__ __forceinline__ void wgmma_n64(float (&d)[32], uint64_t da, uint64_t db, int scaleD) {
  asm volatile("{\n.reg .pred p;\nsetp.ne.b32 p, %34, 0;\n"
    "wgmma.mma_async.sync.aligned.m64n64k16.f32.bf16.bf16 {%0, %1, %2, %3, %4, %5, %6, %7, %8, %9, %10, %11, %12, %13, %14, %15, %16, %17, %18, %19, %20, %21, %22, %23, %24, %25, %26, %27, %28, %29, %30, %31}, %32, %33, p, 1, 1, %35, %36;\n}\n"
    : "+f"(d[0]), "+f"(d[1]), "+f"(d[2]), "+f"(d[3]), "+f"(d[4]), "+f"(d[5]), "+f"(d[6]), "+f"(d[7]), "+f"(d[8]), "+f"(d[9]), "+f"(d[10]), "+f"(d[11]), "+f"(d[12]), "+f"(d[13]), "+f"(d[14]), "+f"(d[15]), "+f"(d[16]), "+f"(d[17]), "+f"(d[18]), "+f"(d[19]), "+f"(d[20]), "+f"(d[21]), "+f"(d[22]), "+f"(d[23]), "+f"(d[24]), "+f"(d[25]), "+f"(d[26]), "+f"(d[27]), "+f"(d[28]), "+f"(d[29]), "+f"(d[30]), "+f"(d[31])
    : "l"(da), "l"(db), "r"(scaleD), "n"(TA), "n"(TB));
}

template<int TA, int TB>
__device__ __forceinline__ void wgmma_n96(float (&d)[48], uint64_t da, uint64_t db, int scaleD) {
  asm volatile("{\n.reg .pred p;\nsetp.ne.b32 p, %50, 0;\n"
    "wgmma.mma_async.sync.aligned.m64n96k16.f32.bf16.bf16 {%0, %1, %2, %3, %4, %5, %6, %7, %8, %9, %10, %11, %12, %13, %14, %15, %16, %17, %18, %19, %20, %21, %22, %23, %24, %25, %26, %27, %28, %29, %30, %31, %32, %33, %34, %35, %36, %37, %38, %39, %40, %41, %42, %43, %44, %45, %46, %47}, %48, %49, p, 1, 1, %51, %52;\n}\n"
    : "+f"(d[0]), "+f"(d[1]), "+f"(d[2]), "+f"(d[3]), "+f"(d[4]), "+f"(d[5]), "+f"(d[6]), "+f"(d[7]), "+f"(d[8]), "+f"(d[9]), "+f"(d[10]), "+f"(d[11]), "+f"(d[12]), "+f"(d[13]), "+f"(d[14]), "+f"(d[15]), "+f"(d[16]), "+f"(d[17]), "+f"(d[18]), "+f"(d[19]), "+f"(d[20]), "+f"(d[21]), "+f"(d[22]), "+f"(d[23]), "+f"(d[24]), "+f"(d[25]), "+f"(d[26]), "+f"(d[27]), "+f"(d[28]), "+f"(d[29]), "+f"(d[30]), "+f"(d[31]), "+f"(d[32]), "+f"(d[33]), "+f"(d[34]), "+f"(d[35]), "+f"(d[36]), "+f"(d[37]), "+f"(d[38]), "+f"(d[39]), "+f"(d[40]), "+f"(d[41]), "+f"(d[42]), "+f"(d[43]), "+f"(d[44]), "+f"(d[45]), "+f"(d[46]), "+f"(d[47])
    : "l"(da), "l"(db), "r"(scaleD), "n"(TA), "n"(TB));
}

template<int TA, int TB>
__device__ __forceinline__ void wgmma_n128(float (&d)[64], uint64_t da, uint64_t db, int scaleD) {
  asm volatile("{\n.reg .pred p;\nsetp.ne.b32 p, %66, 0;\n"
    "wgmma.mma_async.sync.aligned.m64n128k16.f32.bf16.bf16 {%0, %1, %2, %3, %4, %5, %6, %7, %8, %9, %10, %11, %12, %13, %14, %15, %16, %17, %18, %19, %20, %21, %22, %23, %24, %25, %26, %27, %28, %29, %30, %31, %32, %33, %34, %35, %36, %37, %38, %39, %40, %41, %42, %43, %44, %45, %46, %47, %48, %49, %50, %51, %52, %53, %54, %55, %56, %57, %58, %59, %60, %61, %62, %63}, %64, %65, p, 1, 1, %67, %68;\n}\n"
    : "+f"(d[0]), "+f"(d[1]), "+f"(d[2]), "+f"(d[3]), "+f"(d[4]), "+f"(d[5]), "+f"(d[6]), "+f"(d[7]), "+f"(d[8]), "+f"(d[9]), "+f"(d[10]), "+f"(d[11]), "+f"(d[12]), "+f"(d[13]), "+f"(d[14]), "+f"(d[15]), "+f"(d[16]), "+f"(d[17]), "+f"(d[18]), "+f"(d[19]), "+f"(d[20]), "+f"(d[21]), "+f"(d[22]), "+f"(d[23]), "+f"(d[24]), "+f"(d[25]), "+f"(d[26]), "+f"(d[27]), "+f"(d[28]), "+f"(d[29]), "+f"(d[30]), "+f"(d[31]), "+f"(d[32]), "+f"(d[33]), "+f"(d[34]), "+f"(d[35]), "+f"(d[36]), "+f"(d[37]), "+f"(d[38]), "+f"(d[39]), "+f"(d[40]), "+f"(d[41]), "+f"(d[42]), "+f"(d[43]), "+f"(d[44]), "+f"(d[45]), "+f"(d[46]), "+f"(d[47]), "+f"(d[48]), "+f"(d[49]), "+f"(d[50]), "+f"(d[51]), "+f"(d[52]), "+f"(d[53]), "+f"(d[54]), "+f"(d[55]), "+f"(d[56]), "+f"(d[57]), "+f"(d[58]), "+f"(d[59]), "+f"(d[60]), "+f"(d[61]), "+f"(d[62]), "+f"(d[63])
    : "l"(da), "l"(db), "r"(scaleD), "n"(TA), "n"(TB));
}

template<int TA, int TB>
__device__ __forceinline__ void wgmma_n192(float (&d)[96], uint64_t da, uint64_t db, int scaleD) {
  asm volatile("{\n.reg .pred p;\nsetp.ne.b32 p, %98, 0;\n"
    "wgmma.mma_async.sync.aligned.m64n192k16.f32.bf16.bf16 {%0, %1, %2, %3, %4, %5, %6, %7, %8, %9, %10, %11, %12, %13, %14, %15, %16, %17, %18, %19, %20, %21, %22, %23, %24, %25, %26, %27, %28, %29, %30, %31, %32, %33, %34, %35, %36, %37, %38, %39, %40, %41, %42, %43, %44, %45, %46, %47, %48, %49, %50, %51, %52, %53, %54, %55, %56, %57, %58, %59, %60, %61, %62, %63, %64, %65, %66, %67, %68, %69, %70, %71, %72, %73, %74, %75, %76, %77, %78, %79, %80, %81, %82, %83, %84, %85, %86, %87, %88, %89, %90, %91, %92, %93, %94, %95}, %96, %97, p, 1, 1, %99, %100;\n}\n"
    : "+f"(d[0]), "+f"(d[1]), "+f"(d[2]), "+f"(d[3]), "+f"(d[4]), "+f"(d[5]), "+f"(d[6]), "+f"(d[7]), "+f"(d[8]), "+f"(d[9]), "+f"(d[10]), "+f"(d[11]), "+f"(d[12]), "+f"(d[13]), "+f"(d[14]), "+f"(d[15]), "+f"(d[16]), "+f"(d[17]), "+f"(d[18]), "+f"(d[19]), "+f"(d[20]), "+f"(d[21]), "+f"(d[22]), "+f"(d[23]), "+f"(d[24]), "+f"(d[25]), "+f"(d[26]), "+f"(d[27]), "+f"(d[28]), "+f"(d[29]), "+f"(d[30]), "+f"(d[31]), "+f"(d[32]), "+f"(d[33]), "+f"(d[34]), "+f"(d[35]), "+f"(d[36]), "+f"(d[37]), "+f"(d[38]), "+f"(d[39]), "+f"(d[40]), "+f"(d[41]), "+f"(d[42]), "+f"(d[43]), "+f"(d[44]), "+f"(d[45]), "+f"(d[46]), "+f"(d[47]), "+f"(d[48]), "+f"(d[49]), "+f"(d[50]), "+f"(d[51]), "+f"(d[52]), "+f"(d[53]), "+f"(d[54]), "+f"(d[55]), "+f"(d[56]), "+f"(d[57]), "+f"(d[58]), "+f"(d[59]), "+f"(d[60]), "+f"(d[61]), "+f"(d[62]), "+f"(d[63]), "+f"(d[64]), "+f"(d[65]), "+f"(d[66]), "+f"(d[67]), "+f"(d[68]), "+f"(d[69]), "+f"(d[70]), "+f"(d[71]), "+f"(d[72]), "+f"(d[73]), "+f"(d[74]), "+f"(d[75]), "+f"(d[76]), "+f"(d[77]), "+f"(d[78]), "+f"(d[79]), "+f"(d[80]), "+f"(d[81]), "+f"(d[82]), "+f"(d[83]), "+f"(d[84]), "+f"(d[85]), "+f"(d[86]), "+f"(d[87]), "+f"(d[88]), "+f"(d[89]), "+f"(d[90]), "+f"(d[91]), "+f"(d[92]), "+f"(d[93]), "+f"(d[94]), "+f"(d[95])
    : "l"(da), "l"(db), "r"(scaleD), "n"(TA), "n"(TB));
}

template <int BN, int TA, int TB>
struct WG;
template <int TA, int TB> struct WG<96, TA, TB> { static __device__ __forceinline__ void mma(float (&d)[48], uint64_t a, uint64_t b) { wgmma_n96<TA, TB>(d, a, b, 1); } };
template <int TA, int TB> struct WG<128, TA, TB> { static __device__ __forceinline__ void mma(float (&d)[64], uint64_t a, uint64_t b) { wgmma_n128<TA, TB>(d, a, b, 1); } };
template <int TA, int TB> struct WG<192, TA, TB> { static __device__ __forceinline__ void mma(float (&d)[96], uint64_t a, uint64_t b) { wgmma_n192<TA, TB>(d, a, b, 1); } };

__device__ bf16 g_h[S_LEN * D_DIM];
__device__ bf16 g_o[S_LEN * D_DIM];
__device__ bf16 g_x2[S_LEN * D_DIM];
__device__ bf16 g_u[D_DIM * F_DIM];
__device__ uint4 g_statsA[S_LEN * 8];
__device__ uint4 g_statsB[S_LEN * 8];
__device__ uint4 g_halo[256 * 256];
__device__ uint4 g_cs[8 * 1536];
__device__ __align__(128) unsigned g_sync[32];
#define EPOCH() (*(volatile unsigned*)&g_sync[0] >> 11)

#define PRE_NS 400
#define POLL_NS 100
#define HALO_NS 40
#define SKEL 0
#define SUD 1000
#define GRP 0
#define U1D 0
#define VAR 1
#define RHI 232
#define RLO 40
#define HOLD 0
#define PNORM 1
#define TV 1
#define FV 1
#define PREW 1
#define EPOLL 1
#define DP2 1
#define DP3A 1
#define DP3B 1
#define DP4 1
#define CK 0
#define P1POLL 0
#define SPREAD 1
#define XP 3
#define NT 3
#define FASTP 1
#define PROWS 32
#define PACE 1

#define TRC(wg, r, i)
#define TRG(wg, r)
#define TRE(wg, id)
#define TRA(wg, id)

__device__ __forceinline__ float tanh_fast(float x) {
  float y;
  asm("tanh.approx.f32 %0, %1;" : "=f"(y) : "f"(x));
  return y;
}
#define GELU_C 0.3292034911525734f
#define GELU_B 2.423681954311584f
__device__ __forceinline__ float gelu_tanh(float y, float kb) {
  return fmaf(y, tanh_fast(y * fmaf(y, y, kb)), y);
}
__device__ __forceinline__ float ex2_fast(float x) {
  float y;
  asm("ex2.approx.ftz.f32 %0, %1;" : "=f"(y) : "f"(x));
  return y;
}
__device__ __forceinline__ float rcp_fast(float x) {
  float y;
  asm("rcp.approx.ftz.f32 %0, %1;" : "=f"(y) : "f"(x));
  return y;
}
__device__ __forceinline__ uint32_t pack2(float a, float b) {
  __nv_bfloat162 v = __floats2bfloat162_rn(a, b);
  return *reinterpret_cast<uint32_t*>(&v);
}
__device__ __forceinline__ float bf_lo(uint32_t v) { return __uint_as_float(v << 16); }
__device__ __forceinline__ float bf_hi(uint32_t v) { return __uint_as_float(v & 0xffff0000u); }
__device__ __forceinline__ void unpack8(const uint4& t, float (&f)[8]) {
  f[0] = bf_lo(t.x); f[1] = bf_hi(t.x); f[2] = bf_lo(t.y); f[3] = bf_hi(t.y);
  f[4] = bf_lo(t.z); f[5] = bf_hi(t.z); f[6] = bf_lo(t.w); f[7] = bf_hi(t.w);
}
__device__ __forceinline__ uint4 pack8(const float (&f)[8]) {
  return make_uint4(pack2(f[0], f[1]), pack2(f[2], f[3]), pack2(f[4], f[5]), pack2(f[6], f[7]));
}
__device__ __forceinline__ int opaque_tid() { int v; asm volatile("mov.u32 %0, %tid.x;" : "=r"(v)); return v; }
__device__ __forceinline__ uint4 lds128(uint32_t a) {
  uint4 v;
  asm volatile("ld.shared.v4.u32 {%0,%1,%2,%3}, [%4];" : "=r"(v.x), "=r"(v.y), "=r"(v.z), "=r"(v.w) : "r"(a) : "memory");
  return v;
}
__device__ __forceinline__ float2 lds64f(uint32_t a) {
  float2 v;
  asm volatile("ld.shared.v2.f32 {%0,%1}, [%2];" : "=f"(v.x), "=f"(v.y) : "r"(a) : "memory");
  return v;
}
__device__ __forceinline__ uint32_t lds32(uint32_t a) {
  uint32_t v;
  asm volatile("ld.shared.u32 %0, [%1];" : "=r"(v) : "r"(a) : "memory");
  return v;
}
__device__ __forceinline__ void sts128(uint32_t a, const uint4& v) {
  asm volatile("st.shared.v4.u32 [%0], {%1,%2,%3,%4};" ::"r"(a), "r"(v.x), "r"(v.y), "r"(v.z), "r"(v.w) : "memory");
}
__device__ __forceinline__ void sts32(uint32_t a, uint32_t x) {
  asm volatile("st.shared.u32 [%0], %1;" ::"r"(a), "r"(x) : "memory");
}
__device__ __forceinline__ void sts64(uint32_t a, uint32_t x, uint32_t y) {
  asm volatile("st.shared.v2.u32 [%0], {%1,%2};" ::"r"(a), "r"(x), "r"(y) : "memory");
}
__device__ __forceinline__ void sts64f(uint32_t a, float x, float y) {
  asm volatile("st.shared.v2.f32 [%0], {%1,%2};" ::"r"(a), "f"(x), "f"(y) : "memory");
}
__device__ __forceinline__ void stmatrix4(uint32_t a, uint32_t r0, uint32_t r1, uint32_t r2, uint32_t r3) {
  asm volatile("stmatrix.sync.aligned.m8n8.x4.shared.b16 [%0], {%1,%2,%3,%4};" ::"r"(a), "r"(r0), "r"(r1), "r"(r2), "r"(r3) : "memory");
}
__device__ __forceinline__ void ldmatrix4(uint32_t (&r)[4], uint32_t a) {
  asm volatile("ldmatrix.sync.aligned.m8n8.x4.shared.b16 {%0,%1,%2,%3}, [%4];" : "=r"(r[0]), "=r"(r[1]), "=r"(r[2]), "=r"(r[3]) : "r"(a) : "memory");
}
__device__ __forceinline__ uint32_t movmatrix_t(uint32_t a) {
  uint32_t d;
  asm volatile("movmatrix.sync.aligned.m8n8.trans.b16 %0, %1;" : "=r"(d) : "r"(a));
  return d;
}
__device__ __forceinline__ void mma16816(float (&c)[4], uint32_t a0, uint32_t a1, uint32_t a2, uint32_t a3, uint32_t b0, uint32_t b1) {
  asm volatile("mma.sync.aligned.m16n8k16.row.col.f32.bf16.bf16.f32 {%0,%1,%2,%3}, {%4,%5,%6,%7}, {%8,%9}, {%0,%1,%2,%3};"
               : "+f"(c[0]), "+f"(c[1]), "+f"(c[2]), "+f"(c[3]) : "r"(a0), "r"(a1), "r"(a2), "r"(a3), "r"(b0), "r"(b1));
}
__device__ __forceinline__ void mma1688(float (&c)[4], uint32_t a0, uint32_t a1, uint32_t b0) {
  asm volatile("mma.sync.aligned.m16n8k8.row.col.f32.bf16.bf16.f32 {%0,%1,%2,%3}, {%4,%5}, {%6}, {%0,%1,%2,%3};"
               : "+f"(c[0]), "+f"(c[1]), "+f"(c[2]), "+f"(c[3]) : "r"(a0), "r"(a1), "r"(b0));
}
__device__ __forceinline__ uint4 ld_volatile4(const uint4* p) {
  uint4 v;
  asm volatile("ld.relaxed.gpu.global.v4.u32 {%0,%1,%2,%3}, [%4];" : "=r"(v.x), "=r"(v.y), "=r"(v.z), "=r"(v.w) : "l"(p) : "memory");
  return v;
}
__device__ __forceinline__ void stg128(bf16* p, uint32_t a, uint32_t b, uint32_t c, uint32_t d) {
  asm volatile("st.global.v4.u32 [%0], {%1,%2,%3,%4};" ::"l"(p), "r"(a), "r"(b), "r"(c), "r"(d) : "memory");
}
__device__ __forceinline__ void quad_transpose(uint32_t& p0, uint32_t& p1, uint32_t& p2, uint32_t& p3, int t) {
  const bool odd = t & 1, hi = t & 2;
  const uint32_t r0 = __shfl_xor_sync(0xffffffffu, odd ? p0 : p1, 1), r1 = __shfl_xor_sync(0xffffffffu, odd ? p2 : p3, 1);
  const uint32_t ae = odd ? r0 : p0, ao = odd ? p1 : r0, be = odd ? r1 : p2, bo = odd ? p3 : r1;
  const uint32_t v0 = __shfl_xor_sync(0xffffffffu, hi ? ae : be, 2), v1 = __shfl_xor_sync(0xffffffffu, hi ? ao : bo, 2);
  p0 = hi ? v0 : ae; p1 = hi ? v1 : ao; p2 = hi ? be : v0; p3 = hi ? bo : v1;
}
__device__ __forceinline__ void fence_proxy_async_smem() { asm volatile("fence.proxy.async.shared::cta;" ::: "memory"); }
__device__ __forceinline__ void spin_until(const unsigned* p, unsigned target) {
  asm volatile(
      "{\n.reg .pred p;\n.reg .u32 v, c;\nmov.u32 c, 0;\n"
      "SPIN_LOOP:\n"
      "ld.relaxed.gpu.global.u32 v, [%0];\n"
      "sub.u32 v, v, %1;\n"
      "setp.ge.s32 p, v, 0;\n"
      "@p bra.uni SPIN_DONE;\n"
      "add.u32 c, c, 1;\n"
      "setp.lt.u32 p, c, 4194304;\n"
      "@p bra.uni SPIN_LOOP;\n"
      "trap;\n"
      "SPIN_DONE:\n"
      "fence.acquire.gpu;\n}\n" ::"l"(p), "r"(target) : "memory");
}
__device__ __forceinline__ void e_expect_tx(uint32_t bar, uint32_t bytes) {
  asm volatile("{\n.reg .pred p;\nelect.sync _|p, 0xffffffff;\n@p mbarrier.arrive.expect_tx.shared::cta.b64 _, [%0], %1;\n}\n" ::"r"(bar), "r"(bytes) : "memory");
}
__device__ __forceinline__ void e_tma_load(uint32_t dst, const CUtensorMap* tm, uint32_t bar, int c0, int c1, int c3, int c4, uint64_t pol) {
  asm volatile(
      "{\n.reg .pred p;\nelect.sync _|p, 0xffffffff;\n"
      "@p cp.async.bulk.tensor.5d.shared::cluster.global.mbarrier::complete_tx::bytes.L2::cache_hint [%0], [%1, {%3, %4, %5, %6, %7}], [%2], %8;\n}\n" ::"r"(dst),
      "l"((uint64_t)tm), "r"(bar), "r"(c0), "r"(c1), "r"(0), "r"(c3), "r"(c4), "l"(pol) : "memory");
}
#define POL_NORMAL 0x1000000000000000ull
#define POL_FIRST 0x12F0000000000000ull
__device__ __forceinline__ void e_arrive(uint32_t bar) {
  asm volatile("{\n.reg .pred p;\nelect.sync _|p, 0xffffffff;\n@p mbarrier.arrive.shared::cta.b64 _, [%0];\n}\n" ::"r"(bar) : "memory");
}
__device__ __forceinline__ void e_red_release(unsigned* p, unsigned inc) {
  asm volatile("{\n.reg .pred p;\nfence.proxy.async;\nelect.sync _|p, 0xffffffff;\n@p red.relaxed.gpu.global.add.u32 [%0], %1;\n}\n" ::"l"(p), "r"(inc) : "memory");
}

#define RING_U 28
#define OFF_EXT (25 * 8192)
#define OFF_HALO (OFF_EXT + 10240)
#define OFF_BAR (RING_U * 8192)
#define RING_LIM(c) ((0x1c1918 >> ((c) * 8)) & 31)
#define OFF_FULL (OFF_BAR)
#define OFF_EMPTY (OFF_BAR + 192)
#define OFF_STR (OFF_BAR + 256)
#define OFF_OST (OFF_BAR + 272)
#define OFF_TR (OFF_BAR + 288)
#define OFF_TU0 (OFF_BAR + 304)
#define OFF_TU1 (OFF_BAR + 320)
#define OFF_SFR (OFF_BAR + 336)
#define OFF_K01 (OFF_BAR + 352)
#define OFF_RES (OFF_BAR + 368)
#define OFF_DEP (OFF_B2 + 256)
#define OFF_CS (OFF_BAR + 384)
#define OFF_ST (OFF_CS + 768)
#define OFF_B1 (OFF_ST + 576)
#define OFF_B2 (OFF_B1 + 768)
#define SMEM_TOTAL (OFF_B2 + 256 + 80)

enum { K_G1 = 0, K_RES = 2, K_G2 = 4, K_G3 = 6, K_G3S = 8, K_G4 = 9, K_G4S = 11 };
enum { E_O = 1, E_H = 3, E_UA = 5, E_UB = 6, E_U1 = 7, E_X = 8 };
#define MAXSEG 48
#define MAXRUN 32

struct Params {
  CUtensorMap xq[2], wqkv, o_k, wo, h_m, h_1, w1a, w1b, w2, u_k;
  int8_t pair[2][68];
  int nseg;
  uint32_t pre, u0d, u1d, sud, rsd, ef[2];
  uint2 seg[MAXSEG];
  uint32_t run[2][MAXRUN];
};

#define LCTA __shfl_sync(0xffffffffu, (int)lds32(sbase + OFF_K01 + 8), 0)
#define opaque_cta() LCTA

template <int WHICH>
__device__ __forceinline__ void producer(const Params& P, uint32_t sbase) {
  const int cta = LCTA, m = cta >> 3, j = cta & 7;
  uint32_t tail8 = 0;
  const int nseg = P.nseg;
#pragma unroll 1
  for (int si = 0; si < nseg; si++) {
    const uint32_t sg = P.seg[si].x;
    const int kind = sg & 15, n = (sg >> 10) & 63, ks = (((sg >> 16) & 1) + 1) * 64, dep = (sg >> 17) & 31, l = (sg >> 27) & 1;
    const int kk = ((sg >> 4) & 63) * 64;
    const int w = (kind < K_G3S ? kind : kind - 1) & 1;
    const int set = kind == K_G4S ? 2 : w;
    const CUtensorMap* mp;
    int c0 = kk, c1 = kk, c3 = 0, c4 = 0, d0 = 0, d1 = ks, d4 = 0, dx = 0, size, soff;
    uint32_t bytes;
    if (kind < K_G2) {
      size = 5;
      if (WHICH == 0) { mp = &P.wqkv; c0 = m * 64; soff = 16384; bytes = 24576; }
      else { mp = &P.xq[l]; c1 = 0; c3 = w * 16 + j * 2; d0 = ks; d1 = 0; soff = 0; bytes = 16384; }
    } else if (kind < K_G3) {
      size = 3;
      if (WHICH == 0) { mp = &P.wo; c0 = j * 128; c1 = 0; c4 = kk >> 5; d1 = 0; d4 = ks >> 5; dx = 64; soff = 0; bytes = 16384; }
      else { mp = &P.o_k; c1 = (w * 16 + m) * 64; d0 = ks; d1 = 0; soff = 16384; bytes = 8192; }
    } else if (kind < K_G4) {
      size = 4;
      if (WHICH == 0) {
        if (w) { mp = &P.w1b; c0 = 2048 + (m >> 1) * 192; soff = 8192; bytes = 24576; }
        else { mp = &P.w1a; c0 = m * 128; soff = 16384; bytes = 16384; }
      } else {
        soff = 0;
        if (w) { mp = &P.h_1; c0 = j * 128 + (m & 1) * 64; bytes = 8192; }
        else { mp = &P.h_m; c0 = j * 128; bytes = 16384; }
      }
    } else {
      size = kind == K_G4S ? 4 : 3;
      if (WHICH == 0) {
        mp = &P.w2; c1 = 0; c4 = kk >> 5; d1 = 0; d4 = ks >> 5; soff = 16384;
        if (kind == K_G4S) { c0 = m * 64; dx = 1024; bytes = 16384; }
        else { c0 = (w * 16 + m) * 64; bytes = 8192; }
      } else { mp = &P.u_k; c1 = j * 128; d0 = ks; d1 = 0; soff = 0; bytes = 16384; }
    }
    const uint64_t pol = ((P.ef[WHICH] >> (kind + l * 12)) & 1) ? POL_FIRST : POL_NORMAL;
    uint32_t wc = P.seg[si].y;
    const uint32_t fb0 = sbase + OFF_FULL + set * 64, dst0 = sbase + soff, step = size * 8192,
                   dlim = dst0 + (RING_LIM((sg >> 29) & 3) - size) * 8192;
    uint32_t fb = fb0 + (wc >> 29) * 8, dst = dst0 + ((sg >> 22) & 31) * 8192;
    wc = (wc & 0x0fffffffu) | 0x50000000u;
    if (WHICH == 1 && !SKEL && dep) {
      mbar_wait(sbase + OFF_DEP + (dep & 15) * 8, dep >> 4);
      asm volatile("fence.proxy.async.global;" ::: "memory");
    }
#pragma unroll 1
    for (int i = n; i > 0; i--) {
#pragma unroll 1
      for (uint32_t q = wc & 3; q; q--) {
        mbar_wait(sbase + OFF_EMPTY + (tail8 & 0x38), (tail8 >> 6) & 1);
        tail8 += 8;
      }
      e_tma_load(dst, mp, fb, c0, c1, c3, c4, pol);
      if (WHICH == 0 && dx) e_tma_load(dst + 8192, mp, fb, c0 + dx, c1, c3, c4, pol);
      e_expect_tx(fb, bytes);
      wc = (wc >> 2) | 0x40000000u;
      c0 += d0; c1 += d1; c4 += d4;
      fb = fb == fb0 + 56 ? fb0 : fb + 8;
      dst += step;
      if (dst > dlim) dst = dst0;
    }
  }
}

struct Cons {
  uint32_t nsolo, nshr;
  int ri;
  uint32_t prev;
};
template <int MW, int BN, int TA, int TB, int SZ0, int SZ1, int AOFF, int BOFF, int ASH, int BSH, int DP>
__device__ __forceinline__ void gemm_runs(const Params& P, uint32_t sbase, Cons& c, float (&acc)[MW][BN / 2], int wg) {
  uint32_t prev = 0, prev2 = 0;
  uint32_t r;
#pragma unroll
  for (int b = 0; b < MW; b++)
#pragma unroll
    for (int i = 0; i < BN / 2; i++) asm volatile("" : "+f"(acc[b][i])::"memory");
  const bool lead = (threadIdx.x & 127) == 0;
  if (DP == 2) { wgmma_fence(); wgmma_commit(); wgmma_commit(); }
#pragma unroll 1
  do {
    r = P.run[wg][c.ri];
    const int sh = (r >> 14) & 1, pre = (r >> 15) & 15, post = (r >> 19) & 15;
    uint32_t so = ((r >> 6) & 31) * 512, e8 = (r >> 8) & 0x38;
    const uint32_t size = (sh ? SZ1 : SZ0) * 512, slim = RING_LIM((r >> 25) & 3) * 512 - size;
    uint32_t cnt = sh ? c.nshr : c.nsolo;
    const uint32_t fb0 = sbase + OFF_FULL + (sh ? 2 : wg) * 64, eb0 = sbase + OFF_EMPTY + 2 - sh;
    const uint64_t da0 = make_desc(sbase + AOFF + (sh ? ASH * wg : 0), TA ? 8192 : 16, 1024);
    const uint64_t db0 = make_desc(sbase + BOFF + (sh ? BSH * wg : 0), TB ? 8192 : 16, 1024);
    TRC(wg, c.ri, 0);
    if (pre) bar_sync(pre, 256);
    int i = r & 63;
#pragma unroll 1
    do {
      mbar_wait(fb0 + (cnt & 7) * 8, (cnt >> 3) & 1);
      wgmma_fence();
#pragma unroll
      for (int k = 0; k < 4; k++) {
#pragma unroll
        for (int b = 0; b < MW; b++)
          WG<BN, TA, TB>::mma(acc[b], da0 + so + b * 512 + (TA ? k * 128 : k * 2), db0 + so + (TB ? k * 128 : k * 2));
        if (k == (DP == 3 ? CK : 3)) wgmma_commit();
      }
      if (post && i == 1) bar_arrive(post, 256);
      cnt++;
      so += size;
      if (so > slim) so = 0;
      wgmma_wait<DP == 2 ? 2 : 1>();
      const uint32_t rel = DP >= 2 ? prev2 : prev;
      if (rel && lead) mbar_arrive_n(rel & ~7u, rel & 7);
      prev2 = prev;
      prev = eb0 + e8;
      e8 = (e8 + 8) & 0x38;
    } while (--i);
    if (sh) c.nshr = cnt; else c.nsolo = cnt;
    if (r & (1u << 23)) {
      if (DP == 3) wgmma_commit();
      wgmma_wait<0>();
      if (DP >= 2 && prev2 && lead) mbar_arrive_n(prev2 & ~7u, prev2 & 7);
      if (lead) mbar_arrive_n(prev & ~7u, prev & 7);
      prev = prev2 = 0;
    }
    TRC(wg, c.ri, 3);
    c.ri++;
  } while (!(r & (1u << 24)));
  if (BN == 192 && !TA) { c.prev = prev & ~7u; return; }
  if (DP == 3) wgmma_commit();
  wgmma_wait<0>();
#pragma unroll
  for (int b = 0; b < MW; b++)
#pragma unroll
    for (int i = 0; i < BN / 2; i++) asm volatile("" : "+f"(acc[b][i])::"memory");
}

__device__ __forceinline__ void store_tile128(const uint32_t (&pk)[32], bf16* dst, uint32_t bar, int lane) {
#pragma unroll
  for (int i = 0; i < 8; i++) {
    const int o = (i >> 1) * 8 + (i & 1);
    stg128(dst + (i & 1) * 8 * D_DIM + (i >> 1) * 32, pk[o], pk[o + 2], pk[o + 4], pk[o + 6]);
  }
  __syncwarp();
  e_arrive(bar);
}
__device__ __forceinline__ void tile_stats(const float (&acc)[64], uint4* dst, unsigned tag, int t, float z = 0.f) {
  float s0 = z, s1 = z, s2 = z, s3 = z, q0 = z, q1 = z, q2 = z, q3 = z;
#pragma unroll
  for (int j = 0; j < 16; j++) {
    s0 += acc[j * 4 + 0]; s2 += acc[j * 4 + 1]; s1 += acc[j * 4 + 2]; s3 += acc[j * 4 + 3];
    q0 = fmaf(acc[j * 4 + 0], acc[j * 4 + 0], q0); q2 = fmaf(acc[j * 4 + 1], acc[j * 4 + 1], q2);
    q1 = fmaf(acc[j * 4 + 2], acc[j * 4 + 2], q1); q3 = fmaf(acc[j * 4 + 3], acc[j * 4 + 3], q3);
  }
  s0 += s2; s1 += s3; q0 += q2; q1 += q3;
  float s = (t & 1) ? s1 : s0, q = (t & 1) ? q1 : q0;
  s += __shfl_xor_sync(0xffffffffu, (t & 1) ? s0 : s1, 1); q += __shfl_xor_sync(0xffffffffu, (t & 1) ? q0 : q1, 1);
  s += __shfl_xor_sync(0xffffffffu, s, 2); q += __shfl_xor_sync(0xffffffffu, q, 2);
  if (t < 2) __stcg(dst + t * 8, make_uint4(__float_as_uint(s), tag, __float_as_uint(q), tag));
}

__device__ __forceinline__ void attention(const Params& P, float (&acc)[2][96], uint32_t sbase, Cons& c, int wg, int l) {
  const uint32_t r = P.run[wg][c.ri];
  const uint32_t slot0 = sbase + OFF_HALO - 4096;
  TRC(wg, c.ri, 0);
        if (PREW) {
          const int cta = opaque_cta(), tid = opaque_tid();
          if (tid & 32) {
            uint4* hp = &g_halo[((wg * 8 + (cta & 7)) * 16 + (cta >> 3)) * 256 + ((tid >> 6) & 1) * 128 + (tid & 31)];
#pragma unroll
            for (int i = 0; i < 4; i++) __stcg(hp + i * 32, make_uint4(0, 0, 0, 0));
          }
        }
  const uint64_t da0 = make_desc(sbase, 16, 1024), db0 = make_desc(sbase + 16384, 8192, 1024);
  const uint32_t so0 = ((r >> 6) & 31) * 512, so1 = so0 > 15 * 512 ? 0 : so0 + 5 * 512, so2 = so1 > 15 * 512 ? 0 : so1 + 5 * 512;
  {
    uint32_t so = so0;
#pragma unroll 1
    for (int i = 0; i < NT; i++) {
      mbar_wait(sbase + OFF_FULL + wg * 64 + (c.nsolo & 7) * 8, (c.nsolo >> 3) & 1);
      if (i == 0) TRC(wg, c.ri, 2);
      c.nsolo++;
      wgmma_fence();
#pragma unroll
      for (int k = 0; k < 4; k++) WG<192, 0, 1>::mma(acc[1], da0 + so + 512 + k * 2, db0 + so + k * 128);
      wgmma_commit();
      wgmma_wait<1>();
      if (i == 0 && (threadIdx.x & 127) == 0) mbar_arrive_n(c.prev, 2);
      so = so > 15 * 512 ? 0 : so + 5 * 512;
    }
  }
#define TAIL(so)                                                                                                           \
  _Pragma("unroll") for (int k = 0; k < 4; k++) WG<192, 0, 1>::mma(acc[0], da0 + (so) + k * 2, db0 + (so) + k * 128);      \
  wgmma_commit()
#define EB(i) (sbase + OFF_EMPTY + (((r >> 11) + (i)) & 7) * 8)
#define PIN(b, i0, i1) _Pragma("unroll") for (int i = i0; i < i1; i++) asm volatile("" : "+f"(acc[b][i])::"memory")
#define PK(b, jj, h) pack2(acc[b][(jj) * 4 + (h) * 2], acc[b][(jj) * 4 + (h) * 2 + 1])
  mbar_wait(sbase + OFF_STR + wg * 8, l);
  {
    const uint64_t de = (uint64_t)(((sbase + OFF_EXT + wg * 5120) & 0x3FFFF) >> 4) | ((uint64_t)8 << 32);
    wgmma_fence();
    wgmma_n192<0, 0>(acc[1], de + 64, de + 128, 1);
    wgmma_commit();
    wgmma_n192<0, 0>(acc[0], de, de + 128, 1);
  }
  TAIL(so0);
  TAIL(so1);
  const int cta = opaque_cta(), tid = opaque_tid(), lane = tid & 31, g = lane >> 2, t = lane & 3;
  const int wq = __shfl_sync(0xffffffffu, (tid >> 5) & 3, 0), hf = wq & 1;
  const int T = wg * 8 + (cta & 7), tn = cta >> 3;
  uint4* const hp = &g_halo[(T * 16 + tn) * 256 + (wq >> 1) * 128 + lane];
  uint32_t Q[2][8][2], K[2][8][2], V[2][8][2];
#define PACKKV(b)                                                                                       \
  _Pragma("unroll") for (int jj = 7; jj >= 0; jj--) {                                                   \
    V[b][jj][1] = movmatrix_t(PK(b, jj + 16, 1)); V[b][jj][0] = PK(b, jj + 16, 0);                      \
  }                                                                                                     \
  _Pragma("unroll") for (int jj = 7; jj >= 0; jj--) { K[b][jj][1] = PK(b, jj + 8, 1); K[b][jj][0] = PK(b, jj + 8, 0); }
#define PACKQ(b)                                                                                        \
  _Pragma("unroll") for (int jj = 7; jj >= 0; jj--) {                                                   \
    V[b][jj][0] = movmatrix_t(V[b][jj][0]); Q[b][jj][1] = PK(b, jj, 1); Q[b][jj][0] = PK(b, jj, 0);     \
  }
#define HALO_OUT(b, a)                                                                                  \
  sts128(a, make_uint4(K[b][0][1], K[b][1][1], K[b][2][1], K[b][3][1]));                                \
  sts128(a + 512, make_uint4(K[b][4][1], K[b][5][1], K[b][6][1], K[b][7][1]));                          \
  sts128(a + 1024, make_uint4(V[b][0][1], V[b][1][1], V[b][2][1], V[b][3][1]));                         \
  sts128(a + 1536, make_uint4(V[b][4][1], V[b][5][1], V[b][6][1], V[b][7][1]))
  wgmma_wait<2>();
  PIN(1, 0, 96);
  TRE(wg, l * 32 + 1);
  PACKKV(1);
  if (!hf) { HALO_OUT(1, slot0 + (5 + wq) * 2048 + lane * 16); }
  else if (T < 15) {
#pragma unroll
    for (int i = 0; i < 2; i++) {
      __stcg(hp + i * 32, make_uint4(~K[1][i * 4][1], ~K[1][i * 4 + 1][1], ~K[1][i * 4 + 2][1], ~K[1][i * 4 + 3][1]));
      __stcg(hp + (i + 2) * 32, make_uint4(~V[1][i * 4][1], ~V[1][i * 4 + 1][1], ~V[1][i * 4 + 2][1], ~V[1][i * 4 + 3][1]));
    }
  }
  TRE(wg, l * 32 + 2);
  wgmma_fence();
  TAIL(so2);
  wgmma_wait<2>();
  if ((tid & 127) == 0) mbar_arrive_n(EB(0), 2);
  PACKQ(1);
  wgmma_wait<1>();
  if ((r >> 19) & 15) bar_arrive((r >> 19) & 15, 256);
  if ((tid & 127) == 0) mbar_arrive_n(EB(NT - 2), 2);
  const bool o0 = 2 * t > g, o1 = 2 * t + 1 > g;
  float rk[2][4], rq[2][4];
#pragma unroll
  for (int b = 0; b < 2; b++) {
    const uint32_t a = sbase + OFF_ST + ((wq >> 1) * 72 + 8 + b * 32 + hf * 16) * 4;
    const float kscale = 0.17677669529663687f * 1.4426950408889634f;
    const float q0 = __uint_as_float(lds32(a + g * 4)) * kscale, q1 = __uint_as_float(lds32(a + g * 4 + 32)) * kscale;
    const uint32_t a0 = a + t * 8 - (o0 ? 32 : 0), a1 = a + t * 8 + 4 - (o1 ? 32 : 0);
    rk[b][0] = __uint_as_float(lds32(a0)); rk[b][1] = __uint_as_float(lds32(a1));
    rk[b][2] = __uint_as_float(lds32(a0 + 32)); rk[b][3] = __uint_as_float(lds32(a1 + 32));
    rq[b][0] = rk[b][0] * q0; rq[b][1] = rk[b][1] * q0; rq[b][2] = rk[b][2] * q1; rq[b][3] = rk[b][3] * q1;
  }
  const bool remote = !hf && T > 0 && !SKEL;
  uint4 hv[4];
#pragma unroll
  for (int i = 0; i < 4; i++)
    asm volatile("{\n.reg .pred p;\nsetp.ne.u32 p, %5, 0;\nmov.u32 %0, -1;\nmov.u32 %1, -1;\nmov.u32 %2, -1;\nmov.u32 %3, -1;\n"
                 "@p ld.relaxed.gpu.global.v4.u32 {%0,%1,%2,%3}, [%4];\n}\n"
                 : "=&r"(hv[i].x), "=&r"(hv[i].y), "=&r"(hv[i].z), "=&r"(hv[i].w) : "l"(hp - 16 * 256 + i * 32), "r"((int)remote) : "memory");
  wgmma_wait<0>();
  PIN(0, 0, 96);
  if ((tid & 127) == 0) mbar_arrive_n(EB(NT - 1), 2);
  TRC(wg, c.ri, 3);
  c.ri++;
  PACKKV(0);
  HALO_OUT(0, slot0 + (hf ? 3 + wq : 2 + (wq >> 1)) * 2048 + lane * 16);
  PACKQ(0);
  TRE(wg, l * 32 + 29);
  bar_sync(7 + wg, 128);
  uint32_t HK[2][8], HV[2][8];
#pragma unroll
  for (int b = 1; b >= 0; b--) {
    if (b == 1 || hf) {
      const uint32_t a = slot0 + (b ? 4 + wq : 2 + (wq >> 1)) * 2048 + lane * 16;
      const uint4 k0 = lds128(a), k1 = lds128(a + 512), v0 = lds128(a + 1024), v1 = lds128(a + 1536);
      HK[b][0] = k0.x; HK[b][1] = k0.y; HK[b][2] = k0.z; HK[b][3] = k0.w; HK[b][4] = k1.x; HK[b][5] = k1.y; HK[b][6] = k1.z; HK[b][7] = k1.w;
      HV[b][0] = v0.x; HV[b][1] = v0.y; HV[b][2] = v0.z; HV[b][3] = v0.w; HV[b][4] = v1.x; HV[b][5] = v1.y; HV[b][6] = v1.z; HV[b][7] = v1.w;
    } else {
#pragma unroll 1
      for (int it = 0; it < (1 << 20); it++) {
        uint32_t mn = ~0u;
#pragma unroll
        for (int i = 0; i < 4; i++) mn = min(min(mn, min(hv[i].x, hv[i].y)), min(hv[i].z, hv[i].w));
        if (__all_sync(0xffffffffu, mn != 0)) break;
        __nanosleep(HALO_NS);
#pragma unroll
        for (int i = 0; i < 4; i++) hv[i] = ld_volatile4(hp - 16 * 256 + i * 32);
      }
#pragma unroll
      for (int i = 0; i < 2; i++) {
        HK[0][i * 4] = ~hv[i].x; HK[0][i * 4 + 1] = ~hv[i].y; HK[0][i * 4 + 2] = ~hv[i].z; HK[0][i * 4 + 3] = ~hv[i].w;
        HV[0][i * 4] = ~hv[i + 2].x; HV[0][i * 4 + 1] = ~hv[i + 2].y; HV[0][i * 4 + 2] = ~hv[i + 2].z; HV[0][i * 4 + 3] = ~hv[i + 2].w;
      }
    }
  }
  TRE(wg, l * 32 + 3);
  float S[2][2][3][4];
#pragma unroll
  for (int b = 1; b >= 0; b--)
#pragma unroll
    for (int u = 0; u < 2; u++)
#pragma unroll
      for (int kt = 0; kt < 3; kt++) S[b][u][kt][0] = S[b][u][kt][1] = S[b][u][kt][2] = S[b][u][kt][3] = 0.f;
#pragma unroll
  for (int ks = 0; ks < 2; ks++)
#pragma unroll
    for (int b = 1; b >= 0; b--)
#pragma unroll
      for (int u = 0; u < 2; u++) {
        const int j0 = u * 4 + ks * 2;
        mma16816(S[b][u][1], Q[b][j0][0], Q[b][j0][1], Q[b][j0 + 1][0], Q[b][j0 + 1][1], K[b][j0][0], K[b][j0 + 1][0]);
        mma16816(S[b][u][2], Q[b][j0][0], Q[b][j0][1], Q[b][j0 + 1][0], Q[b][j0 + 1][1], K[b][j0][1], K[b][j0 + 1][1]);
        mma16816(S[b][u][0], Q[b][j0][0], Q[b][j0][1], Q[b][j0 + 1][0], Q[b][j0 + 1][1], HK[b][j0], HK[b][j0 + 1]);
      }
  TRE(wg, l * 32 + 4);
  const uint32_t mold = (o0 ? 0xffffu : 0u) | (o1 ? 0xffff0000u : 0u);
  const float NEG = -3.0e38f;
  const bool first = T == 0 && !hf;
  uint32_t pl[2][2], ph[2][2];
#pragma unroll
  for (int b = 1; b >= 0; b--)
#pragma unroll
    for (int u = 0; u < 2; u++) {
      float a0 = (o0 ? S[b][u][0][0] : S[b][u][1][0]) * rq[b][0], a1 = (o1 ? S[b][u][0][1] : S[b][u][1][1]) * rq[b][1];
      float b0 = (o0 ? S[b][u][1][2] : S[b][u][2][2]) * rq[b][2], b1 = (o1 ? S[b][u][1][3] : S[b][u][2][3]) * rq[b][3];
      if (b == 0) { a0 = (first && o0) ? NEG : a0; a1 = (first && o1) ? NEG : a1; }
      float m0 = fmaxf(a0, a1), m1 = fmaxf(b0, b1);
      m0 = fmaxf(m0, __shfl_xor_sync(0xffffffffu, m0, 1)); m1 = fmaxf(m1, __shfl_xor_sync(0xffffffffu, m1, 1));
      m0 = fmaxf(m0, __shfl_xor_sync(0xffffffffu, m0, 2)); m1 = fmaxf(m1, __shfl_xor_sync(0xffffffffu, m1, 2));
      a0 = ex2_fast(a0 - m0); a1 = ex2_fast(a1 - m0); b0 = ex2_fast(b0 - m1); b1 = ex2_fast(b1 - m1);
      float s0 = a0 + a1, s1 = b0 + b1;
      s0 += __shfl_xor_sync(0xffffffffu, s0, 1); s1 += __shfl_xor_sync(0xffffffffu, s1, 1);
      s0 += __shfl_xor_sync(0xffffffffu, s0, 2); s1 += __shfl_xor_sync(0xffffffffu, s1, 2);
      s0 = rcp_fast(s0); s1 = rcp_fast(s1);
      pl[b][u] = pack2(a0 * rk[b][0] * s0, a1 * rk[b][1] * s0); ph[b][u] = pack2(b0 * rk[b][2] * s1, b1 * rk[b][3] * s1);
    }
  float O[2][2][4][4];
#pragma unroll
  for (int b = 1; b >= 0; b--)
#pragma unroll
    for (int u = 0; u < 2; u++)
#pragma unroll
      for (int nt = 0; nt < 4; nt++) {
        O[b][u][nt][0] = O[b][u][nt][1] = O[b][u][nt][2] = O[b][u][nt][3] = 0.f;
        mma1688(O[b][u][nt], pl[b][u] & ~mold, ph[b][u] & mold, V[b][u * 4 + nt][0]);
      }
#pragma unroll
  for (int b = 1; b >= 0; b--)
#pragma unroll
    for (int u = 0; u < 2; u++)
#pragma unroll
      for (int nt = 0; nt < 4; nt++) mma1688(O[b][u][nt], 0u, ph[b][u] & ~mold, V[b][u * 4 + nt][1]);
#pragma unroll
  for (int b = 1; b >= 0; b--)
#pragma unroll
    for (int u = 0; u < 2; u++)
#pragma unroll
      for (int nt = 0; nt < 4; nt++) mma1688(O[b][u][nt], pl[b][u] & mold, 0u, HV[b][u * 4 + nt]);
  {
    uint32_t dep = 0;
#pragma unroll
    for (int i = 0; i < 16; i++) dep |= __float_as_uint(O[i >> 3][(i >> 2) & 1][i & 3][0]);
    bar_arrive(3 + wg + (dep & lds32(sbase + OFF_K01 + 4)), 256);
  }
  TRE(wg, l * 32 + 5);
  bf16* op = g_o + (size_t)(T * 128 + (hf * 16 + g) * 2 + (wq >> 1)) * D_DIM + tn * 64 + t * 8;
#pragma unroll
  for (int b = 1; b >= 0; b--)
#pragma unroll
    for (int u = 0; u < 2; u++)
#pragma unroll
      for (int h = 0; h < 2; h++)
        stg128(op + (b * 64 + h * 16) * D_DIM + u * 32, pack2(O[b][u][0][h * 2], O[b][u][0][h * 2 + 1]), pack2(O[b][u][1][h * 2], O[b][u][1][h * 2 + 1]),
               pack2(O[b][u][2][h * 2], O[b][u][2][h * 2 + 1]), pack2(O[b][u][3][h * 2], O[b][u][3][h * 2 + 1]));
  __syncwarp();
  e_arrive(sbase + OFF_OST + wg * 8);
  if (remote) {
#pragma unroll
    for (int i = 0; i < 4; i++) __stcg(hp - 16 * 256 + i * 32, make_uint4(0, 0, 0, 0));
  }
  TRE(wg, l * 32 + 6);
}

__device__ __forceinline__ uint4 ext_row(float mean) {
  const uint32_t hi = pack2(mean, mean);
  return make_uint4(hi, pack2(mean - bf_lo(hi), 0.f), 0, 0);
}
__device__ __forceinline__ uint4 ext_col(float cs) {
  cs *= -0.5f;
  const float hi = bf_lo(pack2(cs, 0.f));
  return make_uint4(pack2(hi, cs - hi), pack2(hi, 0.f), 0, 0);
}

__device__ __forceinline__ void init_down(float (&acc)[1][64], const uint32_t (&xr)[32], uint32_t sbase) {
  const int tid = opaque_tid();
  uint16_t bb0, bb1;
  const uint32_t ba = sbase + OFF_B2 + ((tid >> 5) * 16 + ((tid & 31) >> 2)) * 2;
  asm volatile("ld.shared.u16 %0, [%1];" : "=h"(bb0) : "r"(ba) : "memory");
  asm volatile("ld.shared.u16 %0, [%1];" : "=h"(bb1) : "r"(ba + 16) : "memory");
  const float k = 2.f * GELU_C, bias0 = __uint_as_float((uint32_t)bb0 << 16) * k, bias1 = __uint_as_float((uint32_t)bb1 << 16) * k;
#pragma unroll
  for (int j = 0; j < 16; j++) {
    acc[0][j * 4 + 0] = fmaf(bf_lo(xr[j * 2]), k, bias0); acc[0][j * 4 + 1] = fmaf(bf_hi(xr[j * 2]), k, bias0);
    acc[0][j * 4 + 2] = fmaf(bf_lo(xr[j * 2 + 1]), k, bias1); acc[0][j * 4 + 3] = fmaf(bf_hi(xr[j * 2 + 1]), k, bias1);
  }
}
template <int W>
__device__ __forceinline__ void mixer_up(const Params& P, uint32_t sbase, Cons& c, int l, float (&acc4)[1][64], const uint32_t (&xr)[32],
                                         const uint32_t (&bw)[24]) {
  constexpr int MW = 2 - W, BN = W ? 192 : 128;
  float acc[MW][BN / 2];
  {
#pragma unroll
    for (int j = 0; j < BN / 8; j++) {
      uint32_t bv;
      asm volatile("mov.b32 %0, %1;" : "=r"(bv) : "r"(bw[j]));
      const float b0 = bf_lo(bv) * GELU_C, b1 = bf_hi(bv) * GELU_C;
#pragma unroll
      for (int b = 0; b < MW; b++) { acc[b][j * 4 + 0] = acc[b][j * 4 + 2] = b0; acc[b][j * 4 + 1] = acc[b][j * 4 + 3] = b1; }
    }
  }
  gemm_runs<MW, BN, 1, 1, 4, 4, 0, MW * 8192, 0, 0, 1>(P, sbase, c, acc, W);
  TRE(W, l * 32 + 16);
  if (W) init_down(acc4, xr, sbase);
  const int cta = opaque_cta(), tid = opaque_tid(), lane = tid & 31;
  bf16* up = g_u + (size_t)((cta & 7) * 128 + (W ? (cta & 8) * 8 : 0) + ((tid >> 5) & 3) * 16 + (lane >> 2)) * F_DIM +
             (W ? 2048 + (cta >> 4) * 192 : (cta >> 3) * 128) + (lane & 3) * 8;
  float k01 = GELU_B, knext = GELU_B;
  const uint32_t r = P.run[W][c.ri];
  uint32_t so = ((r >> 6) & 31) * 512, e8 = (r >> 8) & 0x38;
  const uint64_t da0 = make_desc(sbase + 16384 + 8192, 8192, 1024), db0 = make_desc(sbase, 16, 1024);
  if (W) { TRC(W, c.ri, 0); }
#pragma unroll
  for (int j = 0; j < 8 - W * 2; j++) {
    if (j == 4 && !W) {
      __syncwarp();
      e_arrive(sbase + OFF_TU0);
    }
    if (W) {
      mbar_wait(sbase + OFF_FULL + 128 + (c.nshr & 7) * 8, (c.nshr >> 3) & 1);
      if (j == 0) { TRC(W, c.ri, 2); }
      c.nshr++;
      wgmma_fence();
#pragma unroll
      for (int k = 0; k < 4; k++) WG<128, 1, 0>::mma(acc4[0], da0 + so + k * 128, db0 + so + k * 2);
      wgmma_commit();
      so = so > (RING_LIM((r >> 25) & 3) - 8) * 512 ? 0 : so + 4 * 512;
      if (j) {
        wgmma_wait<1>();
        if ((tid & 127) == 0) mbar_arrive(sbase + OFF_EMPTY + e8);
        e8 = (e8 + 8) & 0x38;
      }
    }
    if (!W && j >= 4) __nanosleep(j == 4 ? P.u0d : P.u1d);
    if (W || j >= 4) k01 = __uint_as_float(lds32(sbase + OFF_K01));
    else k01 = knext;
    if (!W && j < 3) knext = __uint_as_float(lds32(sbase + OFF_K01));
    const int gr = W ? j : j >> 1, mb = W ? 0 : j & 1;
#pragma unroll
    for (int h = 0; h < 2; h++) {
      const float* v = &acc[mb][gr * 16 + h * 2];
      stg128(up + (mb * 64 + h * 8) * F_DIM + gr * 32, pack2(gelu_tanh(v[0], k01), gelu_tanh(v[1], k01)), pack2(gelu_tanh(v[4], k01), gelu_tanh(v[5], k01)),
             pack2(gelu_tanh(v[8], k01), gelu_tanh(v[9], k01)), pack2(gelu_tanh(v[12], k01), gelu_tanh(v[13], k01)));
    }
  }
  __syncwarp();
  e_arrive(sbase + OFF_TU1 + W * 8);
  TRE(W, l * 32 + 17);
  if (W) {
    wgmma_wait<0>();
    if ((tid & 127) == 0) mbar_arrive(sbase + OFF_EMPTY + e8);
#pragma unroll
    for (int i = 0; i < 64; i++) asm volatile("" : "+f"(acc4[0][i])::"memory");
    TRC(W, c.ri, 3);
    c.ri++;
  } else init_down(acc4, xr, sbase);
}

__device__ __forceinline__ void row_stats(const uint4 (&raw)[8], int row0, unsigned tag, int lane) {
  float s[2], q[2];
#pragma unroll
  for (int rr = 0; rr < 2; rr++) {
    s[rr] = 0.f; q[rr] = 0.f;
#pragma unroll
    for (int i = 0; i < 4; i++) {
      float v[8];
      unpack8(raw[rr * 4 + i], v);
      s[rr] += ((v[0] + v[1]) + (v[2] + v[3])) + ((v[4] + v[5]) + (v[6] + v[7]));
#pragma unroll
      for (int e = 0; e < 8; e++) q[rr] = fmaf(v[e], v[e], q[rr]);
    }
  }
#pragma unroll
  for (int o = 16; o > 0; o >>= 1)
#pragma unroll
    for (int rr = 0; rr < 2; rr++) { s[rr] += __shfl_xor_sync(0xffffffffu, s[rr], o); q[rr] += __shfl_xor_sync(0xffffffffu, q[rr], o); }
  const int row = row0 + (lane & 1);
  if (lane < 16)
    __stcg(&g_statsA[((row >> 6) * 8 + (lane >> 1)) * 64 + (row & 63)],
           make_uint4(__float_as_uint(((lane & 1) ? s[1] : s[0]) * 0.125f), tag, __float_as_uint(((lane & 1) ? q[1] : q[0]) * 0.125f), tag));
}
__device__ __forceinline__ uint4 ldg_v(const uint4* p) {
  uint4 v;
  asm volatile("ld.global.nc.v4.u32 {%0,%1,%2,%3}, [%4];" : "=r"(v.x), "=r"(v.y), "=r"(v.z), "=r"(v.w) : "l"(p) : "memory");
  return v;
}
__device__ __noinline__ void startup(const bf16* __restrict__ x, const bf16* __restrict__ wqkv, const bf16* __restrict__ b1,
                                     const bf16* __restrict__ b2, uint32_t sbase, unsigned tag, unsigned delay) {
  const int cta = LCTA, lane = threadIdx.x & 31, wq = __shfl_sync(0xffffffffu, (threadIdx.x >> 5) & 3, 0), m = cta >> 3, j = cta & 7;
  const int i = threadIdx.x & 127, row0 = cta * 8 + wq * 2;
  __nanosleep(delay);
  const uint4* xs = reinterpret_cast<const uint4*>(x + (size_t)row0 * D_DIM) + lane;
  const uint4* ws = reinterpret_cast<const uint4*>(wqkv + (size_t)(j * 128 + wq * 32 + (lane >> 3)) * (3 * D_DIM) + m * 64) + (lane & 7);
  uint4 raw[8], wr[8];
#pragma unroll
  for (int k = 0; k < 8; k++) raw[k] = ldg_v(xs + k * 32);
#pragma unroll
  for (int k = 0; k < 8; k++) wr[k] = ldg_v(ws + k * 4 * 384);
  if (wq < 3) __stcg(&g_cs[j * 1536 + m * 96 + i], make_uint4(0, 0, 0, 0));
  if (i < 40) {
    const uint4 v = *reinterpret_cast<const uint4*>(b1 + (i < 16 ? m * 128 : 1920 + (m >> 1) * 192) + i * 8);
    const uint32_t a = sbase + OFF_B1 + (i < 16 ? i * 4 : 320 + i * 4);
    sts32(a, v.x); sts32(a + 96, v.y); sts32(a + 192, v.z); sts32(a + 288, v.w);
  }
  if (i >= 64 && i < 80) sts128(sbase + OFF_B2 + (i - 64) * 16, *reinterpret_cast<const uint4*>(b2 + (((i >> 3) & 1) * 16 + m) * 64 + (i & 7) * 8));
  const uint32_t sa = sbase + OFF_HALO;
#define WAITFOR(v) if (v[7].x == tag + v[7].y * 65536 + 12345 && v[6].w == 99) delay++
#define COLSUM(v, p)                                                                                                          \
  {                                                                                                                           \
    float s[8];                                                                                                               \
    _Pragma("unroll") for (int e = 0; e < 8; e++) s[e] = 0.f;                                                                 \
    _Pragma("unroll") for (int k = 0; k < 8; k++) {                                                                           \
      float f[8];                                                                                                             \
      unpack8(v[k], f);                                                                                                       \
      _Pragma("unroll") for (int e = 0; e < 8; e++) s[e] += f[e];                                                             \
    }                                                                                                                         \
    const uint32_t a = sa + (wq * 4 + (lane >> 3)) * 768 + (p) * 256 + (lane & 7) * 32;                                       \
    sts128(a, make_uint4(__float_as_uint(s[0]), __float_as_uint(s[1]), __float_as_uint(s[2]), __float_as_uint(s[3])));       \
    sts128(a + 16, make_uint4(__float_as_uint(s[4]), __float_as_uint(s[5]), __float_as_uint(s[6]), __float_as_uint(s[7])));  \
  }
  uint4 w2[8];
  WAITFOR(raw);
#pragma unroll
  for (int k = 0; k < 8; k++) w2[k] = ldg_v(ws + 128 + k * 4 * 384 + (delay >> 31));
  row_stats(raw, row0, tag, lane);
  WAITFOR(wr);
#pragma unroll
  for (int k = 0; k < 8; k++) raw[k] = ldg_v(ws + 256 + k * 4 * 384 + (delay >> 31));
#pragma unroll 1
  for (int p = 0; p < 3; p++) {
    COLSUM(wr, p);
#pragma unroll
    for (int k = 0; k < 8; k++) { wr[k] = w2[k]; w2[k] = raw[k]; }
  }
  bar_sync(8, 128);
  if (wq < 3) {
    float a = 0.f, b = 0.f;
#pragma unroll
    for (int r = 0; r < 16; r++) { const float2 v = lds64f(sa + r * 768 + i * 8); a += v.x; b += v.y; }
    __stcg(&g_cs[j * 1536 + m * 96 + i], make_uint4(__float_as_uint(a), tag, __float_as_uint(b), tag));
  }
  TRE(1, 24);
#pragma unroll
  for (int k = 0; k < 8; k++) raw[k] = ldg_v(xs + 1024 * 128 + k * 32);
#pragma unroll 1
  for (int q = wq == 3 ? 0 : 1; q < 2; q++) {
    const int tk = q ? i : lane - 32;
    const int row = max(j * 128 + tk, 0);
    const uint4* p = &g_statsA[(row >> 6) * 512 + (row & 63)];
    uint4 v;
#pragma unroll 1
    for (int it = 0; it < (1 << 20); it++) {
      v = ld_volatile4(p);
      if (__all_sync(0xffffffffu, v.y == tag && v.w == tag)) break;
      __nanosleep(200);
    }
    const float mean = __uint_as_float(v.x) * (8.0f / D_DIM);
    const float rs = rsqrtf(fmaxf(fmaf(__uint_as_float(v.z), 8.0f / D_DIM, -mean * mean), 0.f) + 1e-5f);
    if (tk >= -16) sts32(sbase + OFF_ST + ((tk & 1) * 72 + 8 + (tk >> 1)) * 4, __float_as_uint(rs));
    if (q) sts128(sbase + OFF_EXT + ((i & 64) + (i & 1) * 32 + ((i & 63) >> 1)) * 16, ext_row(mean));
  }
  if (wq < 3) {
    const uint4* p = &g_cs[m * 96 + i];
    uint4 v[8];
#pragma unroll 1
    for (int it = 0; it < (1 << 20); it++) {
      bool ok = true;
#pragma unroll
      for (int r = 0; r < 8; r++) v[r] = ld_volatile4(p + r * 1536);
#pragma unroll
      for (int r = 0; r < 8; r++) ok = ok && v[r].y == tag && v[r].w == tag;
      if (__all_sync(0xffffffffu, ok)) break;
      __nanosleep(100);
    }
    float a = 0.f, b = 0.f;
#pragma unroll
    for (int r = 0; r < 8; r++) { a += __uint_as_float(v[r].x); b += __uint_as_float(v[r].z); }
    sts64f(sbase + OFF_CS + i * 8, a, b);
    sts128(sbase + OFF_EXT + 2048 + i * 32, ext_col(a));
    sts128(sbase + OFF_EXT + 2048 + i * 32 + 16, ext_col(b));
  }
  if (i == 0) sts32(sbase + OFF_SFR, tag);
  fence_proxy_async_smem();
  bar_sync(8, 128);
  if (i == 0) mbar_arrive(sbase + OFF_STR);
  TRE(1, 27);
  row_stats(raw, row0 + 1024, tag, lane);
  __syncwarp();
}

__device__ __forceinline__ void poll8(uint4 (&v)[8], const uint4* p, int stride, unsigned tag) {
#pragma unroll 1
  for (int it = 0; it < (1 << 20); it++) {
    bool ok = true;
#pragma unroll
    for (int i = 0; i < 8; i++) v[i] = ld_volatile4(p + i * stride);
#pragma unroll
    for (int i = 0; i < 8; i++) ok = ok && v[i].y == tag && v[i].w == tag;
    if (SKEL || __all_sync(0xffffffffu, ok)) break;
    __nanosleep(200);
  }
}

__global__ void __launch_bounds__(384, 1)
mega_kernel(const __grid_constant__ Params P, const bf16* __restrict__ x, const bf16* __restrict__ wqkv, const bf16* __restrict__ b1,
            const bf16* __restrict__ b2, bf16* __restrict__ out) {
  extern __shared__ __align__(1024) uint8_t smem_raw[];
  const uint32_t sbase = smem_u32(smem_raw);
  {
    const int wi = __shfl_sync(0xffffffffu, threadIdx.x >> 5, 0);
    if (wi == 4) {
      uint32_t id, nsm;
      asm volatile("mov.u32 %0, %smid;" : "=r"(id));
      asm volatile("mov.u32 %0, %nsmid;" : "=r"(nsm));
      const bool bysm = gridDim.x == 132 && nsm == 132;
      id = __shfl_sync(0xffffffffu, bysm ? id : blockIdx.x, 0);
      const int lcta = P.pair[bysm][id >> 1] + (id & 1);
      if ((threadIdx.x & 31) == 0) {
#pragma unroll
        for (int s = 0; s < 8; s++) mbar_init(sbase + OFF_FULL + s * 8, 2);
        asm volatile("fence.mbarrier_init.release.cluster;" ::: "memory");
      }
      sts128(sbase + OFF_K01, make_uint4(__float_as_uint(GELU_B), 0, lcta, 0x3f800000));
      __syncwarp();
      bar_arrive(0, 384);
      if (lcta >= 0) {
#pragma unroll 1
        for (int e = 0; e < 5; e++) {
          const uint32_t fb = sbase + OFF_FULL + e * 8;
          e_tma_load(sbase + e * 40960, &P.xq[0], fb, e * 64, 0, (lcta & 7) * 2, 0, POL_NORMAL);
          e_tma_load(sbase + e * 40960 + 16384, &P.wqkv, fb, (lcta >> 3) * 64, e * 64, 0, 0, POL_NORMAL);
          e_expect_tx(fb, 40960);
          e_arrive(fb);
        }
      }
    } else {
      if (wi >= 5 && wi < 11 && (threadIdx.x & 31) == 0) {
      const uint32_t a = sbase + (wi < 9 ? OFF_FULL + (wi - 4) * 64 : wi == 9 ? OFF_TU1 : OFF_DEP + 16);
      const uint32_t c0 = wi < 8 ? 2 : wi == 9 ? 4 : 1, c1 = wi < 8 ? 2 : wi == 8 ? 4 : 1;
      mbar_init(a, c0); mbar_init(a + 8, c0);
      if (wi == 9) { mbar_init(sbase + OFF_DEP, 1); mbar_init(sbase + OFF_DEP + 8, 1); }
      else {
#pragma unroll
        for (int s = 2; s < 8; s++) mbar_init(a + s * 8, c1);
      }
      asm volatile("fence.mbarrier_init.release.cluster;" ::: "memory");
      }
      __syncwarp();
      bar_sync(0, 384);
    }
  }

  if (LCTA < 0) {
    if (threadIdx.x == 0) {
      const unsigned epoch = EPOCH();
#pragma unroll 1
      for (int it = 0; it < (1 << 20) && (int)(*(volatile unsigned*)&g_sync[0] - (epoch * 16 + 1) * NCTA) < 0; it++) __nanosleep(2000);
    }
    return;
  }
  const int warp = __shfl_sync(0xffffffffu, threadIdx.x >> 5, 0);
  const int wg = warp >> 2;
  if (__shfl_sync(0xffffffffu, threadIdx.x >> 8, 0) == 0) {
    asm volatile("setmaxnreg.inc.sync.aligned.u32 %0;" ::"n"(RHI));
    if (wg == 1) startup(x, wqkv, b1, b2, sbase, EPOCH() * 2 + 1, P.sud);
    Cons c;
    c.nsolo = 0; c.nshr = 0; c.ri = 0;
    float acc4[1][64];
#pragma unroll
    for (int i = 0; i < 64; i++) acc4[0][i] = 0.f;
#pragma unroll 1
    for (int l = -1;; l++) {
      if (l >= 0) {
        uint32_t pk[32];
        gemm_runs<1, 128, 1, 0, 3, 4, 16384, 0, 8192, 0, DP4>(P, sbase, c, acc4, wg);
        TRE(wg, l * 32 + 20);
#pragma unroll
        for (int i = 0; i < 64; i++) acc4[0][i] *= 0.5f / GELU_C;
        const int cta = opaque_cta(), tid = opaque_tid(), lane = tid & 31, rw = ((tid >> 5) & 3) * 16;
#pragma unroll
        for (int j = 0; j < 16; j++) {
          pk[j * 2] = pack2(acc4[0][j * 4 + 0], acc4[0][j * 4 + 1]);
          pk[j * 2 + 1] = pack2(acc4[0][j * 4 + 2], acc4[0][j * 4 + 3]);
        }
        store_tile128(pk, (l ? out : g_x2) + (size_t)((wg * 16 + (cta >> 3)) * 64 + rw + (lane >> 2)) * D_DIM + (cta & 7) * 128 + (lane & 3) * 8,
                      sbase + OFF_TR + wg * 8, lane);
        TRE(wg, l * 32 + 21);
        if (l == 0) tile_stats(acc4[0], &g_statsA[(wg * 16 + (cta >> 3)) * 512 + (cta & 7) * 64 + rw + (lane >> 2)], lds32(sbase + OFF_SFR) + 1, lane & 3,
                               __uint_as_float(lds32(sbase + OFF_K01 + 4)));
        TRE(wg, l * 32 + 22);
        if (l) break;
      }
      l++;
      {
        float acc[2][96];
#pragma unroll
        for (int b = 0; b < 2; b++)
#pragma unroll
          for (int i = 0; i < 96; i++) acc[b][i] = 0.f;
        gemm_runs<2, 192, 0, 1, 5, 5, 0, 16384, 0, 0, 1>(P, sbase, c, acc, wg);
        attention(P, acc, sbase, c, wg, l);
      }
      uint32_t bw[24];
      uint32_t xr[32];
      {
        float acc[1][64];
        {
          if (PREW) {
            const int cta = opaque_cta(), tid = opaque_tid();
            if ((tid & 3) < 2) __stcg(&g_statsB[(wg * 16 + (cta >> 3)) * 512 + (cta & 7) * 64 + ((tid >> 5) & 3) * 16 + ((tid & 31) >> 2) + (tid & 3) * 8], make_uint4(0, 0, 0, 0));
          }
          const int cta = opaque_cta(), tid = opaque_tid();
          const uint4* rp = reinterpret_cast<const uint4*>((l ? g_x2 : x) + (size_t)((wg * 16 + (cta >> 3)) * 64 + ((tid >> 5) & 3) * 16 + ((tid & 31) >> 2)) * D_DIM +
                                                           (cta & 7) * 128) + (tid & 3);
          __nanosleep(P.rsd);
          uint4 q[8];
#pragma unroll
          for (int i = 0; i < 8; i++) q[i] = __ldcg(rp + (i & 1) * D_DIM + (i >> 1) * 4);
#pragma unroll
          for (int i = 0; i < 8; i++) {
            quad_transpose(q[i].x, q[i].y, q[i].z, q[i].w, tid & 3);
            float* a = &acc[0][(i >> 1) * 16 + (i & 1) * 2];
            a[0] = bf_lo(q[i].x); a[1] = bf_hi(q[i].x); a[4] = bf_lo(q[i].y); a[5] = bf_hi(q[i].y);
            a[8] = bf_lo(q[i].z); a[9] = bf_hi(q[i].z); a[12] = bf_lo(q[i].w); a[13] = bf_hi(q[i].w);
          }
        }
        gemm_runs<1, 128, 0, 1, 3, 3, 16384, 0, 0, 0, DP2>(P, sbase, c, acc, wg);
        TRE(wg, l * 32 + 10);
        const int cta = opaque_cta(), tid = opaque_tid(), lane = tid & 31, rw = ((tid >> 5) & 3) * 16;
        const unsigned tag = lds32(sbase + OFF_SFR) + l;
        uint4* sb = &g_statsB[(wg * 16 + (cta >> 3)) * 512 + rw];
        tile_stats(acc[0], sb + (cta & 7) * 64 + (lane >> 2), tag, lane & 3);
        TRE(wg, l * 32 + 11);
#pragma unroll
        for (int j = 0; j < 16; j++) {
          xr[j * 2] = pack2(acc[0][j * 4 + 0], acc[0][j * 4 + 1]);
          xr[j * 2 + 1] = pack2(acc[0][j * 4 + 2], acc[0][j * 4 + 3]);
        }
#define XTR(i) quad_transpose(xr[((i) >> 1) * 8 + ((i) & 1)], xr[((i) >> 1) * 8 + ((i) & 1) + 2], xr[((i) >> 1) * 8 + ((i) & 1) + 4], xr[((i) >> 1) * 8 + ((i) & 1) + 6], lane & 3)
        const uint4* sp = sb + (lane & 1) * 256 + (lane >> 1);
        __nanosleep(P.pre);
        uint4 a = ld_volatile4(sp), b = ld_volatile4(sp + 64), cc = ld_volatile4(sp + 128), d = ld_volatile4(sp + 192);
#pragma unroll
        for (int i = 0; i < 8; i++) XTR(i);
#pragma unroll
        for (int j = 0; j < 6; j++) {
          const uint4 v = lds128(sbase + OFF_B1 + wg * 384 + (lane & 3) * 96 + j * 16);
          bw[j * 4] = v.x; bw[j * 4 + 1] = v.y; bw[j * 4 + 2] = v.z; bw[j * 4 + 3] = v.w;
        }
#pragma unroll 1
        for (int it = 0; it < (1 << 20); it++) {
          const bool ok = a.y == tag && a.w == tag && b.y == tag && b.w == tag && cc.y == tag && cc.w == tag && d.y == tag && d.w == tag;
          if (SKEL || __all_sync(0xffffffffu, ok)) break;
          a = ld_volatile4(sp); b = ld_volatile4(sp + 64); cc = ld_volatile4(sp + 128); d = ld_volatile4(sp + 192);
        }
        __syncwarp();
        TRE(wg, l * 32 + 12);
        float mean = (__uint_as_float(a.x) + __uint_as_float(b.x)) + (__uint_as_float(cc.x) + __uint_as_float(d.x));
        float v = (__uint_as_float(a.z) + __uint_as_float(b.z)) + (__uint_as_float(cc.z) + __uint_as_float(d.z));
        mean += __shfl_xor_sync(0xffffffffu, mean, 1);
        v += __shfl_xor_sync(0xffffffffu, v, 1);
        mean *= (1.0f / D_DIM);
        v = fmaxf(fmaf(v, 1.0f / D_DIM, -mean * mean), 0.f);
        const float rs = GELU_C * rsqrtf(fmaf(v + 1e-5f, 1e-5f, v));
        mean *= -rs;
        const int g2 = (lane >> 2) * 2;
        const float nm0 = __shfl_sync(0xffffffffu, mean, g2), rs0 = __shfl_sync(0xffffffffu, rs, g2);
        const float nm1 = __shfl_sync(0xffffffffu, mean, g2 + 16), rs1 = __shfl_sync(0xffffffffu, rs, g2 + 16);
        uint32_t hk[32];
#pragma unroll
        for (int j = 0; j < 16; j++) {
          hk[j * 2] = pack2(fmaf(acc[0][j * 4 + 0], rs0, nm0), fmaf(acc[0][j * 4 + 1], rs0, nm0));
          hk[j * 2 + 1] = pack2(fmaf(acc[0][j * 4 + 2], rs1, nm1), fmaf(acc[0][j * 4 + 3], rs1, nm1));
        }
        store_tile128(hk, g_h + (size_t)((wg * 16 + (cta >> 3)) * 64 + rw + (lane >> 2)) * D_DIM + (cta & 7) * 128 + (lane & 3) * 8, sbase + OFF_TR + wg * 8, lane);
        TRE(wg, l * 32 + 13);
      }
      if (wg == 1) mixer_up<1>(P, sbase, c, l, acc4, xr, bw);
      else mixer_up<0>(P, sbase, c, l, acc4, xr, bw);
      l--;
    }
    TRE(wg, 62);
    TRG(wg, 62);
  } else {
    asm volatile("setmaxnreg.dec.sync.aligned.u32 %0;" ::"n"(RLO));
    if (warp < 10) {
      if (warp == 8) producer<0>(P, sbase);
      else producer<1>(P, sbase);
    } else {
      const unsigned epoch = __shfl_sync(0xffffffffu, EPOCH(), 0);
      const int cta = LCTA, w = warp - 10, j = cta & 7;
      unsigned* const cn = &g_sync[w];
      unsigned tgt = epoch << 11;
      if (w == 1 && (threadIdx.x & 31) < 11) prefetch_tmap(reinterpret_cast<const CUtensorMap*>(&P) + (threadIdx.x & 31));
      __syncwarp();
#pragma unroll 1
      for (int q9 = 0; q9 < 9; q9++) {
        const int l = q9 >= 5, q = q9 - l * 5;
        if (q == 0 && (w | l)) {
          const int lane = opaque_tid() & 31;
          const uint32_t half = sbase + OFF_EXT + (opaque_tid() & 32) * 160;
          mbar_wait(sbase + OFF_OST + 8 - w * 8, w ? l : 0);
#pragma unroll 1
          for (int r = 0; r < 6; r++) sts128(half + 2048 + (r * 32 + lane) * 16, ext_col(__uint_as_float(lds32(sbase + OFF_CS + (r * 32 + lane) * 4))));
#pragma unroll 1
          for (int t0 = -32; t0 < 128; t0 += 32) {
            float mean = 0.f, var = 0.f;
            {
              const int row = max((w * 8 + j) * 128 + t0 + lane, 0);
              uint4 v[8];
              poll8(v, &g_statsA[(row >> 6) * 512 + (row & 63)], 64, epoch * 2 + l + 1);
#pragma unroll
              for (int i = 0; i < 8; i++) { mean += __uint_as_float(v[i].x); var += __uint_as_float(v[i].z); }
            }
            const int tk = t0 + (opaque_tid() & 31);
            mean *= (1.0f / D_DIM);
            const float rs = rsqrtf(fmaxf(fmaf(var, 1.0f / D_DIM, -mean * mean), 0.f) + 1e-5f);
            if (tk >= -16) sts32(sbase + OFF_ST + ((tk & 1) * 72 + 8 + (tk >> 1)) * 4, __float_as_uint(rs));
            if (t0 >= 0) sts128(half + ((tk & 64) + (tk & 1) * 32 + ((tk & 63) >> 1)) * 16, ext_row(mean));
          }
          fence_proxy_async_smem();
          __syncwarp();
          e_arrive(sbase + OFF_STR + w * 8);
          TRA(w, l * 32 + 8);
        }
        if (w && q == 2) continue;
        mbar_wait(sbase + OFF_OST + (q == 4 ? 1 : q) * 16 + w * 8, q == 1 ? 0 : q == 4 ? 1 : l);
        TRA(w, l * 32 + ((0x1c001a0e07ull >> (q * 8)) & 31));
        const unsigned inc = q9 == 8 ? 8 + 2 * w : 1;
        e_red_release(cn, inc);
        TRA(w, l * 32 + ((0x1713120f09ull >> (q * 8)) & 31));
        spin_until(cn, tgt += inc * NCTA);
        e_arrive(sbase + OFF_DEP + (((0x86531 >> (q * 4)) & 15) + w) * 8);
      }
    }
  }
}

typedef CUresult (*PFN_encodeTiled)(CUtensorMap*, CUtensorMapDataType, cuuint32_t, void*, const cuuint64_t*,
                                    const cuuint64_t*, const cuuint32_t*, const cuuint32_t*, CUtensorMapInterleave,
                                    CUtensorMapSwizzle, CUtensorMapL2promotion, CUtensorMapFloatOOBfill);
static PFN_encodeTiled g_encode = nullptr;

static CUtensorMap make_map5(const void* ptr, int d0, int d1, int d2, int d3, int d4, int s1, int s2, int s3, int s4, int b1, int b2, int b3, int b4) {
  CUtensorMap m;
  cuuint64_t dims[5] = {(cuuint64_t)d0, (cuuint64_t)d1, (cuuint64_t)d2, (cuuint64_t)d3, (cuuint64_t)d4};
  cuuint64_t strides[4] = {(cuuint64_t)s1 * 2, (cuuint64_t)s2 * 2, (cuuint64_t)s3 * 2, (cuuint64_t)s4 * 2};
  cuuint32_t box[5] = {64, (cuuint32_t)b1, (cuuint32_t)b2, (cuuint32_t)b3, (cuuint32_t)b4};
  cuuint32_t es[5] = {1, 1, 1, 1, 1};
  g_encode(&m, CU_TENSOR_MAP_DATA_TYPE_BFLOAT16, 5, (void*)ptr, dims, strides, box, es, CU_TENSOR_MAP_INTERLEAVE_NONE,
           CU_TENSOR_MAP_SWIZZLE_128B, CU_TENSOR_MAP_L2_PROMOTION_L2_128B, CU_TENSOR_MAP_FLOAT_OOB_FILL_NONE);
  return m;
}
static CUtensorMap make_map(const void* ptr, int rows, int cols, int box_rows, int nblk = 1, int bstep = 64) {
  return make_map5(ptr, cols - (nblk - 1) * bstep, rows, nblk, 1, 1, cols, bstep, 64, 64, box_rows, nblk, 1, 1);
}
static CUtensorMap make_map_perm(const void* ptr, int rows, int cols) {
  return make_map5(ptr, cols, 2, 4, 4, rows / 32, cols, 8 * cols, 2 * cols, 32 * cols, 2, 4, 4, 2);
}

#define tune(n, d) (d)
#define PX tune("PX", 6)
#define PA1 tune("PA1", 1)
#define PY tune("PY", 8)
#define PB1 tune("PB1", 2)
#define PZ tune("PZ", 16)
#define PV tune("PV", 16)
#define PA4 tune("PA4", 12)

struct Sched {
  Params& P;
  int pos = 0, e = 0, nr[2] = {0, 0}, l = 0;
  int cap[12] = {8, 8, 8, 8, tune("C2", 8), tune("C2", 8), 8, tune("C3", 8), 8, tune("C4", 8), tune("C4", 8), 8};
  int lastk[2] = {-1, -1}, laste[2] = {0, 0};
  int tail = 0, cnt[3] = {0, 0, 0}, owner[RING_U], big = 0, lastlc = -1;
  Sched(Params& p) : P(p) { P.nseg = 0; for (int u = 0; u < RING_U; u++) owner[u] = -1; }
  void add(int kind, int k0, int n, int dep, int pre, int post, int fl, int ks = 1, int x = 0) {
    if (n <= 0) return;
    static const int size[12] = {5, 5, 3, 3, 3, 3, 4, 4, 6, 3, 3, 4};
    const int sz = size[kind], sh = kind == K_G4S, w = (kind < K_G3S ? kind : kind - 1) & 1, set = sh ? 2 : w;
    const int lc = kind < K_G2 ? 1 : big * 2, lim = RING_LIM(lc), pad = lc != lastlc;
    lastlc = lc;
    if (tune("ALN", 1)) pos = (pos + sz - 1) / sz * sz;
    if (pos + sz > lim) pos = 0;
    for (int v = 0; v < 2; v++)
      if (sh || v == w) {
        const int last = ((fl >> (2 + v)) & 1) | (fl >> 4), drain = ((fl >> v) & 1) | ((fl >> (2 + v)) & 1);
        const int pr = sh && !v ? 0 : pre, po = sh && v ? 0 : post;
        if (nr[v] && lastk[v] == kind && laste[v] == e && !pad && !pr && !(x & (v ? 19 : 3)) && !(P.run[v][nr[v] - 1] & 0x11f80000u) && !tune("NOMERGE", 0)) {
          P.run[v][nr[v] - 1] += n | po << 19 | drain << 23 | last << 24;
          laste[v] = e + n;
          continue;
        }
        lastk[v] = kind; laste[v] = e + n;
        P.run[v][nr[v]++] = n | pos << 6 | (e & 7) << 11 | sh << 14 | (sh && !v ? 0 : pre) << 15 | (sh && v ? 0 : post) << 19 | drain << 23 | last << 24 |
                            lc << 25 | (v ? x >> 4 : 0) << 28;
      }
    int i0 = 0;
    const uint32_t px = P.nseg ? P.seg[P.nseg - 1].x : ~0u;
    if (!pad && P.nseg && (int)(px & 15) == kind && !dep && (int)((px >> 16) & 1) == ks - 1 && (int)(((px >> 4) & 63) + ((px >> 10) & 63) * ks) == k0) {
      i0 = (px >> 10) & 63;
      P.seg[P.nseg - 1].x += n << 10;
    } else P.seg[P.nseg++] = make_uint2(kind | k0 << 4 | n << 10 | (ks - 1) << 16 | dep << 17 | pos << 22 | l << 27 | lc << 29, (cnt[set] & 7) << 29);
    for (int i = i0; i < i0 + n; i++) {
      int need = e - cap[kind];
      for (int u = pos; u < pos + sz; u++) { if (owner[u] > need) need = owner[u]; owner[u] = e; }
      int nw = need + 1 > tail ? need + 1 - tail : 0;
      if (i >= 14 && nw == 0) nw = 1;
      if (nw > 3 || (i >= 14 && nw != 1)) P.nseg = -1000000;
      if (i < 14) P.seg[P.nseg - 1].y |= nw << (2 * i);
      tail += nw;
      e++;
      pos += sz;
      if (i + 1 < i0 + n && pos + sz > lim) pos = 0;
    }
    cnt[set] += n;
  }
};

static void build_schedule(Params& P) {
  Sched s(P);
  for (int t0 = 0; t0 < 66; t0++) {
    const int g8 = t0 >> 2, mq = g8 >> 2, jq = (mq & 1) ? 3 - (g8 & 3) : (g8 & 3), emu = tune("MAP", 0);
    P.pair[0][t0] = t0 < 64 ? (mq * 4 + (t0 & 3)) * 8 + jq * 2 : -2;
    int t = t0;
    if (emu && t >= 60 && t != 62 && t != 65) t = t < 62 ? t + 3 : t - 3;
    const int g = t < 32 ? t & 7 : t < 60 ? 1 + (t - 32) % 7 : 0, p = t < 32 ? t >> 3 : t < 60 ? 4 + (t - 32) / 7 : t - 58;
    const int q = ((emu == 1 ? 0x64752310 : 0x75642310) >> (g * 4)) & 7, cp = p % 3;
    P.pair[1][t0] = t == 60 || t == 61 ? -2 : ((q >> 1) * 4 + (cp == 2 ? 3 : p / 3)) * 8 + (q & 1) * 4 + (cp == 2 ? p / 3 : cp) * 2;
  }
  P.u1d = tune("U1D", 200);
  P.ef[0] = tune("EFW", 0);
  P.ef[1] = tune("EFA", 0);
  P.rsd = tune("RSD", 500);
  P.u0d = tune("U0D", 500);
  P.sud = tune("SUD", 500);
  P.pre = tune("PRE", 250);
  const int sk4 = tune("SK4", 6);
  for (int l = 0; l < 2; l++) {
    s.l = l;
    const int b = l * 16, a4 = l ? tune("PA4L", 0) : PA4;
    s.add(K_G1, 0, 16 - NT, l ? E_X : 0, 0, 0, 16);
    s.add(K_G1, 16 - NT, NT, 0, 0, 1, 0);
    s.add(K_G1 + 1, 0, PA1, l ? E_X + 1 : 0, 1, 0, 3);
    s.add(K_G1 + 1, PA1, PX - PA1, 0, 3, 0, 3);
    s.add(K_G2, 0, 16, b + E_O, 0, 1, 12);
    s.add(K_G1 + 1, PX, 16 - NT - PX, 0, 1, 0, 16);
    s.add(K_G1 + 1, 16 - NT, NT, 0, 0, PB1 ? 2 : 0, 0);
    s.add(K_G3, 0, PB1, b + E_H, 2, 0, 3);
    s.add(K_G3, PB1, PY - PB1, PB1 ? 0 : b + E_H, 4, 0, 3);
    s.add(K_G2 + 1, 0, 16, b + E_O + 1, 0, 2, 12);
    s.big = tune("BIG", 1);
    s.add(K_G3, PY, 16 - PY, 0, 2, 0, 3);
    const int pv = PV, pw = tune("PW", 0);
    s.add(K_G3 + 1, 0, PZ, 0, 0, 0, 3);
    s.add(K_G3, 16, pv, b + E_H + 1, 0, pv == 16, pv == 16 ? 12 : 3);
    s.add(K_G3 + 1, PZ, pv == 16 ? 0 : pw, 0, 0, 0, 3);
    s.add(K_G3, 16 + pv, 16 - pv, 0, 0, 1, 12);
    s.add(K_G3 + 1, PZ + (pv == 16 ? 0 : pw), 32 - PZ - (pv == 16 ? 0 : pw), 0, 1, 0, 12);
    const int k4 = l ? tune("SK4L", 5) : sk4;
    s.add(K_G4S, 0, 6, b + E_UA, 0, 0, 0, 2, 16);
    s.add(K_G4S, 12, 10, 0, 0, 0, 0, 2);
    s.add(K_G4S, 1, 16, b + E_UB, 0, 0, a4 ? 2 : 0, 2);
    s.add(K_G4, 32, a4, b + E_U1, 0, 0, 0);
    s.add(K_G4S, 32 + a4, 17 - a4, a4 ? 0 : b + E_U1, 0, 0, 0);
    if (l == 0) s.big = 0;
    s.add(K_G4S, 49, 7 - k4, 0, 0, 0, k4 ? 2 : a4 ? 4 : 12);
    s.add(K_G4S, 56 - k4, k4, 0, 1, 1, a4 ? 4 : 12);
    s.add(K_G4 + 1, 32, a4, 0, 0, 0, 12);
  }
  P.seg[0].x = P.seg[0].x + (5 << 4) - (5 << 10);
  P.seg[0].y = 0x05555555u | 5u << 29;
}

extern "C" void kernel_launch(void* const* d_in, const int* in_sizes, int n_in, void* d_out, int out_size) {
  const bf16* x = (const bf16*)d_in[0];
  const bf16* wqkv = (const bf16*)d_in[1];
  const bf16* wo = (const bf16*)d_in[2];
  const bf16* w1 = (const bf16*)d_in[4];
  const bf16* b1 = (const bf16*)d_in[5];
  const bf16* w2 = (const bf16*)d_in[6];
  const bf16* b2 = (const bf16*)d_in[7];
  bf16* out = (bf16*)d_out;

  if (!g_encode) {
    void* fn = nullptr;
    cudaDriverEntryPointQueryResult st;
    cudaGetDriverEntryPoint("cuTensorMapEncodeTiled", &fn, cudaEnableDefault, &st);
    g_encode = (PFN_encodeTiled)fn;
  }
  bf16 *h, *o, *u, *x2;
  cudaGetSymbolAddress((void**)&h, g_h);
  cudaGetSymbolAddress((void**)&o, g_o);
  cudaGetSymbolAddress((void**)&u, g_u);
  cudaGetSymbolAddress((void**)&x2, g_x2);
  Params P;
  P.xq[0] = make_map5(x, D_DIM, 32, 2, 32, 1, 2 * D_DIM, D_DIM, 64 * D_DIM, 64, 32, 2, 2, 1);
  P.xq[1] = make_map5(x2, D_DIM, 32, 2, 32, 1, 2 * D_DIM, D_DIM, 64 * D_DIM, 64, 32, 2, 2, 1);
  P.wqkv = make_map(wqkv, D_DIM, 3 * D_DIM, 64, 3, 1024);
  P.o_k = make_map(o, S_LEN, D_DIM, 64);
  P.wo = make_map_perm(wo, D_DIM, D_DIM);
  P.h_m = make_map(h, S_LEN, D_DIM, 64, 2);
  P.h_1 = make_map(h, S_LEN, D_DIM, 64);
  P.w1a = make_map(w1, S_LEN, F_DIM, 64, 2);
  P.w1b = make_map(w1, S_LEN, F_DIM, 64, 3);
  P.w2 = make_map_perm(w2, F_DIM, S_LEN);
  P.u_k = make_map(u, D_DIM, F_DIM, 128);
  build_schedule(P);
  cudaFuncSetAttribute(mega_kernel, cudaFuncAttributeMaxDynamicSharedMemorySize, SMEM_TOTAL);
  int sms = 0;
  cudaDeviceGetAttribute(&sms, cudaDevAttrMultiProcessorCount, 0);
  mega_kernel<<<sms == 132 && tune("G132", 1) ? 132 : NCTA, 384, SMEM_TOTAL, cudaStreamPerThread>>>(P, x, wqkv, b1, b2, out);
}
```

```cpp
#include <cuda_runtime.h>
#include <cuda_bf16.h>
#include <cuda.h>
#include <stdint.h>

typedef __nv_bfloat16 bf16;

#define S_LEN 2048
#define D_DIM 1024
#define F_DIM 3584
#define NCTA 128

__device__ __forceinline__ uint32_t smem_u32(const void* p) { return (uint32_t)__cvta_generic_to_shared(p); }
__device__ __forceinline__ void mbar_init(uint32_t bar, uint32_t count) {
  asm volatile("mbarrier.init.shared::cta.b64 [%0], %1;" ::"r"(bar), "r"(count) : "memory");
}
__device__ __forceinline__ void mbar_arrive(uint32_t bar) {
  asm volatile("mbarrier.arrive.shared::cta.b64 _, [%0];" ::"r"(bar) : "memory");
}
__device__ __forceinline__ void mbar_arrive_n(uint32_t bar, uint32_t n) {
  asm volatile("mbarrier.arrive.shared::cta.b64 _, [%0], %1;" ::"r"(bar), "r"(n) : "memory");
}
__device__ __forceinline__ void mbar_wait(uint32_t bar, uint32_t parity) {
  asm volatile(
      "{\n.reg .pred p;\n.reg .u32 c;\nmov.u32 c, 0;\n"
      "WAIT_LOOP:\n"
      "mbarrier.try_wait.parity.shared::cta.b64 p, [%0], %1;\n"
      "@p bra.uni WAIT_DONE;\n"
      "add.u32 c, c, 1;\n"
      "setp.lt.u32 p, c, 4194304;\n"
      "@p bra.uni WAIT_LOOP;\n"
      "trap;\n"
      "WAIT_DONE:\n}\n" ::"r"(bar), "r"(parity) : "memory");
}
__device__ __forceinline__ void prefetch_tmap(const CUtensorMap* tm) {
  asm volatile("prefetch.tensormap [%0];" ::"l"((uint64_t)tm) : "memory");
}
__device__ __forceinline__ void wgmma_fence() { asm volatile("wgmma.fence.sync.aligned;" ::: "memory"); }
__device__ __forceinline__ void wgmma_commit() { asm volatile("wgmma.commit_group.sync.aligned;" ::: "memory"); }
template <int N>
__device__ __forceinline__ void wgmma_wait() { asm volatile("wgmma.wait_group.sync.aligned %0;" ::"n"(N) : "memory"); }
__device__ __forceinline__ void bar_sync(int id, int nthreads) { asm volatile("bar.sync %0, %1;" ::"r"(id), "r"(nthreads) : "memory"); }
__device__ __forceinline__ void bar_arrive(int id, int nthreads) { asm volatile("bar.arrive %0, %1;" ::"r"(id), "r"(nthreads) : "memory"); }
__device__ __forceinline__ uint64_t make_desc(uint32_t addr, uint32_t lbo_bytes, uint32_t sbo_bytes) {
  uint64_t d = 0;
  d |= (uint64_t)((addr & 0x3FFFF) >> 4);
  d |= (uint64_t)((lbo_bytes & 0x3FFFF) >> 4) << 16;
  d |= (uint64_t)((sbo_bytes & 0x3FFFF) >> 4) << 32;
  d |= (uint64_t)1 << 62;
  return d;
}
template<int TA, int TB>
__device__ __forceinline__ void wgmma_n64(float (&d)[32], uint64_t da, uint64_t db, int scaleD) {
  asm volatile("{\n.reg .pred p;\nsetp.ne.b32 p, %34, 0;\n"
    "wgmma.mma_async.sync.aligned.m64n64k16.f32.bf16.bf16 {%0, %1, %2, %3, %4, %5, %6, %7, %8, %9, %10, %11, %12, %13, %14, %15, %16, %17, %18, %19, %20, %21, %22, %23, %24, %25, %26, %27, %28, %29, %30, %31}, %32, %33, p, 1, 1, %35, %36;\n}\n"
    : "+f"(d[0]), "+f"(d[1]), "+f"(d[2]), "+f"(d[3]), "+f"(d[4]), "+f"(d[5]), "+f"(d[6]), "+f"(d[7]), "+f"(d[8]), "+f"(d[9]), "+f"(d[10]), "+f"(d[11]), "+f"(d[12]), "+f"(d[13]), "+f"(d[14]), "+f"(d[15]), "+f"(d[16]), "+f"(d[17]), "+f"(d[18]), "+f"(d[19]), "+f"(d[20]), "+f"(d[21]), "+f"(d[22]), "+f"(d[23]), "+f"(d[24]), "+f"(d[25]), "+f"(d[26]), "+f"(d[27]), "+f"(d[28]), "+f"(d[29]), "+f"(d[30]), "+f"(d[31])
    : "l"(da), "l"(db), "r"(scaleD), "n"(TA), "n"(TB));
}

template<int TA, int TB>
__device__ __forceinline__ void wgmma_n96(float (&d)[48], uint64_t da, uint64_t db, int scaleD) {
  asm volatile("{\n.reg .pred p;\nsetp.ne.b32 p, %50, 0;\n"
    "wgmma.mma_async.sync.aligned.m64n96k16.f32.bf16.bf16 {%0, %1, %2, %3, %4, %5, %6, %7, %8, %9, %10, %11, %12, %13, %14, %15, %16, %17, %18, %19, %20, %21, %22, %23, %24, %25, %26, %27, %28, %29, %30, %31, %32, %33, %34, %35, %36, %37, %38, %39, %40, %41, %42, %43, %44, %45, %46, %47}, %48, %49, p, 1, 1, %51, %52;\n}\n"
    : "+f"(d[0]), "+f"(d[1]), "+f"(d[2]), "+f"(d[3]), "+f"(d[4]), "+f"(d[5]), "+f"(d[6]), "+f"(d[7]), "+f"(d[8]), "+f"(d[9]), "+f"(d[10]), "+f"(d[11]), "+f"(d[12]), "+f"(d[13]), "+f"(d[14]), "+f"(d[15]), "+f"(d[16]), "+f"(d[17]), "+f"(d[18]), "+f"(d[19]), "+f"(d[20]), "+f"(d[21]), "+f"(d[22]), "+f"(d[23]), "+f"(d[24]), "+f"(d[25]), "+f"(d[26]), "+f"(d[27]), "+f"(d[28]), "+f"(d[29]), "+f"(d[30]), "+f"(d[31]), "+f"(d[32]), "+f"(d[33]), "+f"(d[34]), "+f"(d[35]), "+f"(d[36]), "+f"(d[37]), "+f"(d[38]), "+f"(d[39]), "+f"(d[40]), "+f"(d[41]), "+f"(d[42]), "+f"(d[43]), "+f"(d[44]), "+f"(d[45]), "+f"(d[46]), "+f"(d[47])
    : "l"(da), "l"(db), "r"(scaleD), "n"(TA), "n"(TB));
}

template<int TA, int TB>
__device__ __forceinline__ void wgmma_n128(float (&d)[64], uint64_t da, uint64_t db, int scaleD) {
  asm volatile("{\n.reg .pred p;\nsetp.ne.b32 p, %66, 0;\n"
    "wgmma.mma_async.sync.aligned.m64n128k16.f32.bf16.bf16 {%0, %1, %2, %3, %4, %5, %6, %7, %8, %9, %10, %11, %12, %13, %14, %15, %16, %17, %18, %19, %20, %21, %22, %23, %24, %25, %26, %27, %28, %29, %30, %31, %32, %33, %34, %35, %36, %37, %38, %39, %40, %41, %42, %43, %44, %45, %46, %47, %48, %49, %50, %51, %52, %53, %54, %55, %56, %57, %58, %59, %60, %61, %62, %63}, %64, %65, p, 1, 1, %67, %68;\n}\n"
    : "+f"(d[0]), "+f"(d[1]), "+f"(d[2]), "+f"(d[3]), "+f"(d[4]), "+f"(d[5]), "+f"(d[6]), "+f"(d[7]), "+f"(d[8]), "+f"(d[9]), "+f"(d[10]), "+f"(d[11]), "+f"(d[12]), "+f"(d[13]), "+f"(d[14]), "+f"(d[15]), "+f"(d[16]), "+f"(d[17]), "+f"(d[18]), "+f"(d[19]), "+f"(d[20]), "+f"(d[21]), "+f"(d[22]), "+f"(d[23]), "+f"(d[24]), "+f"(d[25]), "+f"(d[26]), "+f"(d[27]), "+f"(d[28]), "+f"(d[29]), "+f"(d[30]), "+f"(d[31]), "+f"(d[32]), "+f"(d[33]), "+f"(d[34]), "+f"(d[35]), "+f"(d[36]), "+f"(d[37]), "+f"(d[38]), "+f"(d[39]), "+f"(d[40]), "+f"(d[41]), "+f"(d[42]), "+f"(d[43]), "+f"(d[44]), "+f"(d[45]), "+f"(d[46]), "+f"(d[47]), "+f"(d[48]), "+f"(d[49]), "+f"(d[50]), "+f"(d[51]), "+f"(d[52]), "+f"(d[53]), "+f"(d[54]), "+f"(d[55]), "+f"(d[56]), "+f"(d[57]), "+f"(d[58]), "+f"(d[59]), "+f"(d[60]), "+f"(d[61]), "+f"(d[62]), "+f"(d[63])
    : "l"(da), "l"(db), "r"(scaleD), "n"(TA), "n"(TB));
}

template<int TA, int TB>
__device__ __forceinline__ void wgmma_n192(float (&d)[96], uint64_t da, uint64_t db, int scaleD) {
  asm volatile("{\n.reg .pred p;\nsetp.ne.b32 p, %98, 0;\n"
    "wgmma.mma_async.sync.aligned.m64n192k16.f32.bf16.bf16 {%0, %1, %2, %3, %4, %5, %6, %7, %8, %9, %10, %11, %12, %13, %14, %15, %16, %17, %18, %19, %20, %21, %22, %23, %24, %25, %26, %27, %28, %29, %30, %31, %32, %33, %34, %35, %36, %37, %38, %39, %40, %41, %42, %43, %44, %45, %46, %47, %48, %49, %50, %51, %52, %53, %54, %55, %56, %57, %58, %59, %60, %61, %62, %63, %64, %65, %66, %67, %68, %69, %70, %71, %72, %73, %74, %75, %76, %77, %78, %79, %80, %81, %82, %83, %84, %85, %86, %87, %88, %89, %90, %91, %92, %93, %94, %95}, %96, %97, p, 1, 1, %99, %100;\n}\n"
    : "+f"(d[0]), "+f"(d[1]), "+f"(d[2]), "+f"(d[3]), "+f"(d[4]), "+f"(d[5]), "+f"(d[6]), "+f"(d[7]), "+f"(d[8]), "+f"(d[9]), "+f"(d[10]), "+f"(d[11]), "+f"(d[12]), "+f"(d[13]), "+f"(d[14]), "+f"(d[15]), "+f"(d[16]), "+f"(d[17]), "+f"(d[18]), "+f"(d[19]), "+f"(d[20]), "+f"(d[21]), "+f"(d[22]), "+f"(d[23]), "+f"(d[24]), "+f"(d[25]), "+f"(d[26]), "+f"(d[27]), "+f"(d[28]), "+f"(d[29]), "+f"(d[30]), "+f"(d[31]), "+f"(d[32]), "+f"(d[33]), "+f"(d[34]), "+f"(d[35]), "+f"(d[36]), "+f"(d[37]), "+f"(d[38]), "+f"(d[39]), "+f"(d[40]), "+f"(d[41]), "+f"(d[42]), "+f"(d[43]), "+f"(d[44]), "+f"(d[45]), "+f"(d[46]), "+f"(d[47]), "+f"(d[48]), "+f"(d[49]), "+f"(d[50]), "+f"(d[51]), "+f"(d[52]), "+f"(d[53]), "+f"(d[54]), "+f"(d[55]), "+f"(d[56]), "+f"(d[57]), "+f"(d[58]), "+f"(d[59]), "+f"(d[60]), "+f"(d[61]), "+f"(d[62]), "+f"(d[63]), "+f"(d[64]), "+f"(d[65]), "+f"(d[66]), "+f"(d[67]), "+f"(d[68]), "+f"(d[69]), "+f"(d[70]), "+f"(d[71]), "+f"(d[72]), "+f"(d[73]), "+f"(d[74]), "+f"(d[75]), "+f"(d[76]), "+f"(d[77]), "+f"(d[78]), "+f"(d[79]), "+f"(d[80]), "+f"(d[81]), "+f"(d[82]), "+f"(d[83]), "+f"(d[84]), "+f"(d[85]), "+f"(d[86]), "+f"(d[87]), "+f"(d[88]), "+f"(d[89]), "+f"(d[90]), "+f"(d[91]), "+f"(d[92]), "+f"(d[93]), "+f"(d[94]), "+f"(d[95])
    : "l"(da), "l"(db), "r"(scaleD), "n"(TA), "n"(TB));
}

template <int BN, int TA, int TB>
struct WG;
template <int TA, int TB> struct WG<96, TA, TB> { static __device__ __forceinline__ void mma(float (&d)[48], uint64_t a, uint64_t b) { wgmma_n96<TA, TB>(d, a, b, 1); } };
template <int TA, int TB> struct WG<128, TA, TB> { static __device__ __forceinline__ void mma(float (&d)[64], uint64_t a, uint64_t b, int s = 1) { wgmma_n128<TA, TB>(d, a, b, s); } };
template <int TA, int TB> struct WG<192, TA, TB> { static __device__ __forceinline__ void mma(float (&d)[96], uint64_t a, uint64_t b, int s = 1) { wgmma_n192<TA, TB>(d, a, b, s); } };

#define g_h g_o
__device__ bf16 g_o[S_LEN * D_DIM];
__device__ bf16 g_x2[S_LEN * D_DIM];
__device__ bf16 g_u[D_DIM * F_DIM];
__device__ uint4 g_statsA[S_LEN * 8];
__device__ uint4 g_statsB[S_LEN * 8];
__device__ uint4 g_halo[256 * 256];
__device__ uint4 g_cs[8 * 1536];
__device__ __align__(128) unsigned g_sync[32];
#define EPOCH() (*(volatile unsigned*)&g_sync[0] >> 11)

#define PRE_NS 400
#define POLL_NS 100
#define HALO_NS 40
#define SKEL 0
#define SUD 1000
#define GRP 0
#define U1D 0
#define VAR 1
#define RHI 232
#define RLO 40
#define HOLD 0
#define PNORM 1
#define TV 1
#define FV 1
#define PREW 1
#define EPOLL 1
#define DP2 1
#define DP3A 1
#define DP3B 1
#define DP4 1
#define CK 0
#define P1POLL 0
#define SPREAD 1
#define XP 3
#define NT 3
#define FASTP 1
#define PFK 2
#define PROWS 32
#define PACE 1

#define TRC(wg, r, i)
#define TRG(wg, r)
#define TRE(wg, id)
#define TRA(wg, id)

__device__ __forceinline__ float tanh_fast(float x) {
  float y;
  asm("tanh.approx.f32 %0, %1;" : "=f"(y) : "f"(x));
  return y;
}
#define GELU_C 0.3292034911525734f
#define GELU_B 2.423681954311584f
__device__ __forceinline__ float gelu_tanh(float y, float kb) {
  return fmaf(y, tanh_fast(y * fmaf(y, y, kb)), y);
}
__device__ __forceinline__ float ex2_fast(float x) {
  float y;
  asm("ex2.approx.ftz.f32 %0, %1;" : "=f"(y) : "f"(x));
  return y;
}
__device__ __forceinline__ float rcp_fast(float x) {
  float y;
  asm("rcp.approx.ftz.f32 %0, %1;" : "=f"(y) : "f"(x));
  return y;
}
__device__ __forceinline__ uint32_t pack2(float a, float b) {
  __nv_bfloat162 v = __floats2bfloat162_rn(a, b);
  return *reinterpret_cast<uint32_t*>(&v);
}
__device__ __forceinline__ float bf_lo(uint32_t v) { return __uint_as_float(v << 16); }
__device__ __forceinline__ float bf_hi(uint32_t v) { return __uint_as_float(v & 0xffff0000u); }
__device__ __forceinline__ void unpack8(const uint4& t, float (&f)[8]) {
  f[0] = bf_lo(t.x); f[1] = bf_hi(t.x); f[2] = bf_lo(t.y); f[3] = bf_hi(t.y);
  f[4] = bf_lo(t.z); f[5] = bf_hi(t.z); f[6] = bf_lo(t.w); f[7] = bf_hi(t.w);
}
__device__ __forceinline__ uint4 pack8(const float (&f)[8]) {
  return make_uint4(pack2(f[0], f[1]), pack2(f[2], f[3]), pack2(f[4], f[5]), pack2(f[6], f[7]));
}
__device__ __forceinline__ int opaque_tid() { int v; asm volatile("mov.u32 %0, %tid.x;" : "=r"(v)); return v; }
__device__ __forceinline__ uint4 lds128(uint32_t a) {
  uint4 v;
  asm volatile("ld.shared.v4.u32 {%0,%1,%2,%3}, [%4];" : "=r"(v.x), "=r"(v.y), "=r"(v.z), "=r"(v.w) : "r"(a) : "memory");
  return v;
}
__device__ __forceinline__ float2 lds64f(uint32_t a) {
  float2 v;
  asm volatile("ld.shared.v2.f32 {%0,%1}, [%2];" : "=f"(v.x), "=f"(v.y) : "r"(a) : "memory");
  return v;
}
__device__ __forceinline__ uint32_t lds32(uint32_t a) {
  uint32_t v;
  asm volatile("ld.shared.u32 %0, [%1];" : "=r"(v) : "r"(a) : "memory");
  return v;
}
__device__ __forceinline__ void sts128(uint32_t a, const uint4& v) {
  asm volatile("st.shared.v4.u32 [%0], {%1,%2,%3,%4};" ::"r"(a), "r"(v.x), "r"(v.y), "r"(v.z), "r"(v.w) : "memory");
}
__device__ __forceinline__ void sts32(uint32_t a, uint32_t x) {
  asm volatile("st.shared.u32 [%0], %1;" ::"r"(a), "r"(x) : "memory");
}
__device__ __forceinline__ void sts64(uint32_t a, uint32_t x, uint32_t y) {
  asm volatile("st.shared.v2.u32 [%0], {%1,%2};" ::"r"(a), "r"(x), "r"(y) : "memory");
}
__device__ __forceinline__ void sts64f(uint32_t a, float x, float y) {
  asm volatile("st.shared.v2.f32 [%0], {%1,%2};" ::"r"(a), "f"(x), "f"(y) : "memory");
}
__device__ __forceinline__ void stmatrix4(uint32_t a, uint32_t r0, uint32_t r1, uint32_t r2, uint32_t r3) {
  asm volatile("stmatrix.sync.aligned.m8n8.x4.shared.b16 [%0], {%1,%2,%3,%4};" ::"r"(a), "r"(r0), "r"(r1), "r"(r2), "r"(r3) : "memory");
}
__device__ __forceinline__ void ldmatrix4(uint32_t (&r)[4], uint32_t a) {
  asm volatile("ldmatrix.sync.aligned.m8n8.x4.shared.b16 {%0,%1,%2,%3}, [%4];" : "=r"(r[0]), "=r"(r[1]), "=r"(r[2]), "=r"(r[3]) : "r"(a) : "memory");
}
__device__ __forceinline__ uint32_t movmatrix_t(uint32_t a) {
  uint32_t d;
  asm volatile("movmatrix.sync.aligned.m8n8.trans.b16 %0, %1;" : "=r"(d) : "r"(a));
  return d;
}
__device__ __forceinline__ void mma16816(float (&c)[4], uint32_t a0, uint32_t a1, uint32_t a2, uint32_t a3, uint32_t b0, uint32_t b1) {
  asm volatile("mma.sync.aligned.m16n8k16.row.col.f32.bf16.bf16.f32 {%0,%1,%2,%3}, {%4,%5,%6,%7}, {%8,%9}, {%0,%1,%2,%3};"
               : "+f"(c[0]), "+f"(c[1]), "+f"(c[2]), "+f"(c[3]) : "r"(a0), "r"(a1), "r"(a2), "r"(a3), "r"(b0), "r"(b1));
}
__device__ __forceinline__ void mma1688(float (&c)[4], uint32_t a0, uint32_t a1, uint32_t b0) {
  asm volatile("mma.sync.aligned.m16n8k8.row.col.f32.bf16.bf16.f32 {%0,%1,%2,%3}, {%4,%5}, {%6}, {%0,%1,%2,%3};"
               : "+f"(c[0]), "+f"(c[1]), "+f"(c[2]), "+f"(c[3]) : "r"(a0), "r"(a1), "r"(b0));
}
__device__ __forceinline__ uint4 ld_volatile4(const uint4* p) {
  uint4 v;
  asm volatile("ld.relaxed.gpu.global.v4.u32 {%0,%1,%2,%3}, [%4];" : "=r"(v.x), "=r"(v.y), "=r"(v.z), "=r"(v.w) : "l"(p) : "memory");
  return v;
}
__device__ __forceinline__ void stg128(bf16* p, uint32_t a, uint32_t b, uint32_t c, uint32_t d) {
  asm volatile("st.global.v4.u32 [%0], {%1,%2,%3,%4};" ::"l"(p), "r"(a), "r"(b), "r"(c), "r"(d) : "memory");
}
__device__ __forceinline__ void quad_transpose(uint32_t& p0, uint32_t& p1, uint32_t& p2, uint32_t& p3, int t) {
  const bool odd = t & 1, hi = t & 2;
  const uint32_t r0 = __shfl_xor_sync(0xffffffffu, odd ? p0 : p1, 1), r1 = __shfl_xor_sync(0xffffffffu, odd ? p2 : p3, 1);
  const uint32_t ae = odd ? r0 : p0, ao = odd ? p1 : r0, be = odd ? r1 : p2, bo = odd ? p3 : r1;
  const uint32_t v0 = __shfl_xor_sync(0xffffffffu, hi ? ae : be, 2), v1 = __shfl_xor_sync(0xffffffffu, hi ? ao : bo, 2);
  p0 = hi ? v0 : ae; p1 = hi ? v1 : ao; p2 = hi ? be : v0; p3 = hi ? bo : v1;
}
__device__ __forceinline__ void fence_proxy_async_smem() { asm volatile("fence.proxy.async.shared::cta;" ::: "memory"); }
__device__ __forceinline__ void spin_until(const unsigned* p, unsigned target) {
  asm volatile(
      "{\n.reg .pred p;\n.reg .u32 v, c;\nmov.u32 c, 0;\n"
      "SPIN_LOOP:\n"
      "ld.relaxed.gpu.global.u32 v, [%0];\n"
      "sub.u32 v, v, %1;\n"
      "setp.ge.s32 p, v, 0;\n"
      "@p bra.uni SPIN_DONE;\n"
      "add.u32 c, c, 1;\n"
      "setp.lt.u32 p, c, 4194304;\n"
      "@p bra.uni SPIN_LOOP;\n"
      "trap;\n"
      "SPIN_DONE:\n"
      "fence.acquire.gpu;\n}\n" ::"l"(p), "r"(target) : "memory");
}
__device__ __forceinline__ void e_expect_tx(uint32_t bar, uint32_t bytes) {
  asm volatile("{\n.reg .pred p;\nelect.sync _|p, 0xffffffff;\n@p mbarrier.arrive.expect_tx.shared::cta.b64 _, [%0], %1;\n}\n" ::"r"(bar), "r"(bytes) : "memory");
}
__device__ __forceinline__ void e_tma_load(uint32_t dst, const CUtensorMap* tm, uint32_t bar, int c0, int c1, int c3, int c4, uint64_t pol) {
  asm volatile(
      "{\n.reg .pred p;\nelect.sync _|p, 0xffffffff;\n"
      "@p cp.async.bulk.tensor.5d.shared::cluster.global.mbarrier::complete_tx::bytes.L2::cache_hint [%0], [%1, {%3, %4, %5, %6, %7}], [%2], %8;\n}\n" ::"r"(dst),
      "l"((uint64_t)tm), "r"(bar), "r"(c0), "r"(c1), "r"(0), "r"(c3), "r"(c4), "l"(pol) : "memory");
}
#define POL_NORMAL 0x1000000000000000ull
#define POL_FIRST 0x12F0000000000000ull
__device__ __forceinline__ void e_arrive(uint32_t bar) {
  asm volatile("{\n.reg .pred p;\nelect.sync _|p, 0xffffffff;\n@p mbarrier.arrive.shared::cta.b64 _, [%0];\n}\n" ::"r"(bar) : "memory");
}
__device__ __forceinline__ void e_red_release(unsigned* p, unsigned inc) {
  asm volatile("{\n.reg .pred p;\nfence.proxy.async;\nelect.sync _|p, 0xffffffff;\n@p red.relaxed.gpu.global.add.u32 [%0], %1;\n}\n" ::"l"(p), "r"(inc) : "memory");
}

#define RING_U 28
#define OFF_EXT (25 * 8192)
#define OFF_HALO (OFF_EXT + 10240)
#define OFF_BAR (RING_U * 8192)
#define RING_LIM(c) ((0x1c1918 >> ((c) * 8)) & 31)
#define OFF_FULL (OFF_BAR)
#define OFF_EMPTY (OFF_BAR + 192)
#define OFF_STR (OFF_BAR + 256)
#define OFF_OST (OFF_BAR + 272)
#define OFF_TR (OFF_BAR + 288)
#define OFF_TU0 (OFF_BAR + 304)
#define OFF_TU1 (OFF_BAR + 320)
#define OFF_SFR (OFF_BAR + 336)
#define OFF_K01 (OFF_BAR + 352)
#define OFF_RES (OFF_BAR + 368)
#define OFF_DEP (OFF_B2 + 256)
#define OFF_CS (OFF_BAR + 384)
#define OFF_ST (OFF_CS + 768)
#define OFF_B1 (OFF_ST + 576)
#define OFF_B2 (OFF_B1 + 768)
#define SMEM_TOTAL (OFF_B2 + 256 + 80)

enum { K_G1 = 0, K_RES = 2, K_G2 = 4, K_G3 = 6, K_G3S = 8, K_G4 = 9, K_G4S = 11 };
enum { E_O = 1, E_H = 3, E_UA = 5, E_UB = 6, E_U1 = 7, E_X = 8 };
#define MAXSEG 48
#define MAXRUN 32

struct Params {
  CUtensorMap xq[2], wqkv, o_k, wo, h_m, h_1, w1a, w1b, w2, u_k;
  int8_t pair[2][68];
  int nseg;
  uint32_t ild, pre, u0d, u1d, sud, rsd, ef[2];
  uint2 seg[MAXSEG];
  uint32_t run[2][MAXRUN];
};

#define LCTA __shfl_sync(0xffffffffu, (int)lds32(sbase + OFF_K01 + 8), 0)
#define opaque_cta() LCTA

template <int WHICH>
__device__ __forceinline__ void producer(const Params& P, uint32_t sbase) {
  const int cta = LCTA, m = cta >> 3, j = cta & 7;
  uint32_t tail8 = 0;
  const int nseg = P.nseg;
#pragma unroll 1
  for (int si = 0; si < nseg; si++) {
    const uint32_t sg = P.seg[si].x;
    const int kind = sg & 15, n = (sg >> 10) & 63, ks = (((sg >> 16) & 1) + 1) * 64, dep = (sg >> 17) & 31, l = (sg >> 27) & 1;
    const int kk = ((sg >> 4) & 63) * 64;
    const int w = (kind < K_G3S ? kind : kind - 1) & 1;
    const int set = kind == K_G4S ? 2 : w;
    const CUtensorMap* mp;
    int c0 = kk, c1 = kk, c3 = 0, c4 = 0, d0 = 0, d1 = ks, d4 = 0, dx = 0, size, soff;
    uint32_t bytes;
    if (kind < K_G2) {
      size = 5;
      if (WHICH == 0) { mp = &P.wqkv; c0 = m * 64; soff = 16384; bytes = 24576; }
      else { mp = &P.xq[l]; c1 = 0; c3 = w * 16 + j * 2; d0 = ks; d1 = 0; soff = 0; bytes = 16384; }
    } else if (kind < K_G3) {
      size = 3;
      if (WHICH == 0) { mp = &P.wo; c0 = j * 128; c1 = 0; c4 = kk >> 5; d1 = 0; d4 = ks >> 5; dx = 64; soff = 0; bytes = 16384; }
      else { mp = &P.o_k; c1 = (w * 16 + m) * 64; d0 = ks; d1 = 0; soff = 16384; bytes = 8192; }
    } else if (kind < K_G4) {
      size = 4;
      if (WHICH == 0) {
        if (w) { mp = &P.w1b; c0 = 2048 + (m >> 1) * 192; soff = 8192; bytes = 24576; }
        else { mp = &P.w1a; c0 = m * 128; soff = 16384; bytes = 16384; }
      } else {
        soff = 0;
        if (w) { mp = &P.h_1; c0 = j * 128 + (m & 1) * 64; bytes = 8192; }
        else { mp = &P.h_m; c0 = j * 128; bytes = 16384; }
      }
    } else {
      size = kind == K_G4S ? 4 : 3;
      if (WHICH == 0) {
        mp = &P.w2; c1 = 0; c4 = kk >> 5; d1 = 0; d4 = ks >> 5; soff = 16384;
        if (kind == K_G4S) { c0 = m * 64; dx = 1024; bytes = 16384; }
        else { c0 = (w * 16 + m) * 64; bytes = 8192; }
      } else { mp = &P.u_k; c1 = j * 128; d0 = ks; d1 = 0; soff = 0; bytes = 16384; }
    }
    const uint64_t pol = ((P.ef[WHICH] >> (kind + l * 12)) & 1) ? POL_FIRST : POL_NORMAL;
    uint32_t wc = P.seg[si].y;
    const uint32_t fb0 = sbase + OFF_FULL + set * 64, dst0 = sbase + soff, step = size * 8192,
                   dlim = dst0 + (RING_LIM((sg >> 29) & 3) - size) * 8192;
    uint32_t fb = fb0 + (wc >> 29) * 8, dst = dst0 + ((sg >> 22) & 31) * 8192;
    wc = (wc & 0x0fffffffu) | 0x50000000u;
    if (WHICH == 1 && !SKEL && dep) {
      mbar_wait(sbase + OFF_DEP + (dep & 15) * 8, dep >> 4);
      asm volatile("fence.proxy.async.global;" ::: "memory");
    }
#pragma unroll 1
    for (int i = n; i > 0; i--) {
#pragma unroll 1
      for (uint32_t q = wc & 3; q; q--) {
        mbar_wait(sbase + OFF_EMPTY + (tail8 & 0x38), (tail8 >> 6) & 1);
        tail8 += 8;
      }
      e_tma_load(dst, mp, fb, c0, c1, c3, c4, pol);
      if (WHICH == 0 && dx) e_tma_load(dst + 8192, mp, fb, c0 + dx, c1, c3, c4, pol);
      e_expect_tx(fb, bytes);
      wc = (wc >> 2) | 0x40000000u;
      c0 += d0; c1 += d1; c4 += d4;
      fb = fb == fb0 + 56 ? fb0 : fb + 8;
      dst += step;
      if (dst > dlim) dst = dst0;
    }
  }
}

struct Cons {
  uint32_t nsolo, nshr;
  int ri;
  uint32_t prev;
};
template <int MW, int BN, int TA, int TB, int SZ0, int SZ1, int AOFF, int BOFF, int ASH, int BSH, int DP>
__device__ __forceinline__ void gemm_runs(const Params& P, uint32_t sbase, Cons& c, float (&acc)[MW][BN / 2], int wg) {
  uint32_t prev = 0, prev2 = 0;
  uint32_t r;
#pragma unroll
  for (int b = 0; b < MW; b++)
#pragma unroll
    for (int i = 0; i < BN / 2; i++) asm volatile("" : "+f"(acc[b][i])::"memory");
  const bool lead = (threadIdx.x & 127) == 0;
  if (DP == 2) { wgmma_fence(); wgmma_commit(); wgmma_commit(); }
#pragma unroll 1
  do {
    r = P.run[wg][c.ri];
    const int sh = (r >> 14) & 1, pre = (r >> 15) & 15, post = (r >> 19) & 15;
    uint32_t so = ((r >> 6) & 31) * 512, e8 = (r >> 8) & 0x38;
    const uint32_t size = (sh ? SZ1 : SZ0) * 512, slim = RING_LIM((r >> 25) & 3) * 512 - size;
    uint32_t cnt = sh ? c.nshr : c.nsolo;
    const uint32_t fb0 = sbase + OFF_FULL + (sh ? 2 : wg) * 64, eb0 = sbase + OFF_EMPTY + 2 - sh;
    const uint64_t da0 = make_desc(sbase + AOFF + (sh ? ASH * wg : 0), TA ? 8192 : 16, 1024);
    const uint64_t db0 = make_desc(sbase + BOFF + (sh ? BSH * wg : 0), TB ? 8192 : 16, 1024);
    TRC(wg, c.ri, 0);
    if (pre) bar_sync(pre, 256);
    int i = r & 63;
#pragma unroll 1
    do {
      mbar_wait(fb0 + (cnt & 7) * 8, (cnt >> 3) & 1);
      wgmma_fence();
#pragma unroll
      for (int k = 0; k < 4; k++) {
#pragma unroll
        for (int b = 0; b < MW; b++)
          WG<BN, TA, TB>::mma(acc[b], da0 + so + b * 512 + (TA ? k * 128 : k * 2), db0 + so + (TB ? k * 128 : k * 2));
        if (k == (DP == 3 ? CK : 3)) wgmma_commit();
      }
      if (post && i == 1) bar_arrive(post, 256);
      cnt++;
      so += size;
      if (so > slim) so = 0;
      wgmma_wait<DP == 2 ? 2 : 1>();
      const uint32_t rel = DP >= 2 ? prev2 : prev;
      if (rel && lead) mbar_arrive_n(rel & ~7u, rel & 7);
      prev2 = prev;
      prev = eb0 + e8;
      e8 = (e8 + 8) & 0x38;
    } while (--i);
    if (sh) c.nshr = cnt; else c.nsolo = cnt;
    if (r & (1u << 23)) {
      if (DP == 3) wgmma_commit();
      wgmma_wait<0>();
      if (DP >= 2 && prev2 && lead) mbar_arrive_n(prev2 & ~7u, prev2 & 7);
      if (lead) mbar_arrive_n(prev & ~7u, prev & 7);
      prev = prev2 = 0;
    }
    TRC(wg, c.ri, 3);
    c.ri++;
  } while (!(r & (1u << 24)));
  if (BN == 192 && !TA) { c.prev = prev & ~7u; return; }
  if (DP == 3) wgmma_commit();
  wgmma_wait<0>();
#pragma unroll
  for (int b = 0; b < MW; b++)
#pragma unroll
    for (int i = 0; i < BN / 2; i++) asm volatile("" : "+f"(acc[b][i])::"memory");
}

__device__ __forceinline__ void store_tile128(const uint32_t (&pk)[32], bf16* dst, uint32_t bar, int lane) {
#pragma unroll
  for (int i = 0; i < 8; i++) {
    const int o = (i >> 1) * 8 + (i & 1);
    stg128(dst + (i & 1) * 8 * D_DIM + (i >> 1) * 32, pk[o], pk[o + 2], pk[o + 4], pk[o + 6]);
  }
  __syncwarp();
  e_arrive(bar);
}
template <bool SLOW>
__device__ __forceinline__ void tile_stats(const float (&acc)[64], uint4* dst, unsigned tag, int t, float z = 0.f) {
  float s0 = z, s1 = z, s2 = z, s3 = z, q0 = z, q1 = z, q2 = z, q3 = z;
  if (SLOW) {
#pragma unroll
    for (int j = 0; j < 32; j++) { const float v = acc[(j >> 1) * 4 + (j & 1)]; s0 += v; q0 = fmaf(v, v, q0); }
    s1 = __uint_as_float(__float_as_uint(s0) & __float_as_uint(z)); q1 = __uint_as_float(__float_as_uint(q0) & __float_as_uint(z));
#pragma unroll
    for (int j = 0; j < 32; j++) { const float v = acc[(j >> 1) * 4 + (j & 1) + 2]; s1 += v; q1 = fmaf(v, v, q1); }
  } else
#pragma unroll
  for (int j = 0; j < 16; j++) {
    s0 += acc[j * 4 + 0]; s2 += acc[j * 4 + 1]; s1 += acc[j * 4 + 2]; s3 += acc[j * 4 + 3];
    q0 = fmaf(acc[j * 4 + 0], acc[j * 4 + 0], q0); q2 = fmaf(acc[j * 4 + 1], acc[j * 4 + 1], q2);
    q1 = fmaf(acc[j * 4 + 2], acc[j * 4 + 2], q1); q3 = fmaf(acc[j * 4 + 3], acc[j * 4 + 3], q3);
  }
  s0 += s2; s1 += s3; q0 += q2; q1 += q3;
  float s = (t & 1) ? s1 : s0, q = (t & 1) ? q1 : q0;
  s += __shfl_xor_sync(0xffffffffu, (t & 1) ? s0 : s1, 1); q += __shfl_xor_sync(0xffffffffu, (t & 1) ? q0 : q1, 1);
  s += __shfl_xor_sync(0xffffffffu, s, 2); q += __shfl_xor_sync(0xffffffffu, q, 2);
  if (t < 2) __stcg(dst + t * 8, make_uint4(__float_as_uint(s), tag, __float_as_uint(q), tag));
}

__device__ __forceinline__ void attention(const Params& P, float (&acc)[2][96], uint32_t sbase, Cons& c, int wg, int l) {
  const uint32_t r = P.run[wg][c.ri];
  const uint32_t slot0 = sbase + OFF_HALO - 4096;
  TRC(wg, c.ri, 0);
        if (PREW) {
          const int cta = opaque_cta(), tid = opaque_tid();
          if (tid & 32) {
            uint4* hp = &g_halo[((wg * 8 + (cta & 7)) * 16 + (cta >> 3)) * 256 + ((tid >> 6) & 1) * 128 + (tid & 31)];
#pragma unroll
            for (int i = 0; i < 4; i++) __stcg(hp + i * 32, make_uint4(0, 0, 0, 0));
          }
        }
  const uint64_t da0 = make_desc(sbase, 16, 1024), db0 = make_desc(sbase + 16384, 8192, 1024);
  const uint32_t so0 = ((r >> 6) & 31) * 512, so1 = so0 > 15 * 512 ? 0 : so0 + 5 * 512, so2 = so1 > 15 * 512 ? 0 : so1 + 5 * 512;
  {
    uint32_t so = so0;
#pragma unroll 1
    for (int i = 0; i < NT; i++) {
      mbar_wait(sbase + OFF_FULL + wg * 64 + (c.nsolo & 7) * 8, (c.nsolo >> 3) & 1);
      if (i == 0) TRC(wg, c.ri, 2);
      c.nsolo++;
      wgmma_fence();
#pragma unroll
      for (int k = 0; k < 4; k++) WG<192, 0, 1>::mma(acc[1], da0 + so + 512 + k * 2, db0 + so + k * 128);
      wgmma_commit();
      wgmma_wait<1>();
      if (i == 0 && (threadIdx.x & 127) == 0) mbar_arrive_n(c.prev, 2);
      so = so > 15 * 512 ? 0 : so + 5 * 512;
    }
  }
#define TAIL(so)                                                                                                           \
  _Pragma("unroll") for (int k = 0; k < 4; k++) WG<192, 0, 1>::mma(acc[0], da0 + (so) + k * 2, db0 + (so) + k * 128);      \
  wgmma_commit()
#define EB(i) (sbase + OFF_EMPTY + (((r >> 11) + (i)) & 7) * 8)
#define PIN(b, i0, i1) _Pragma("unroll") for (int i = i0; i < i1; i++) asm volatile("" : "+f"(acc[b][i])::"memory")
#define PK(b, jj, h) pack2(acc[b][(jj) * 4 + (h) * 2], acc[b][(jj) * 4 + (h) * 2 + 1])
  mbar_wait(sbase + OFF_STR + wg * 8, l);
  {
    const uint64_t de = (uint64_t)(((sbase + OFF_EXT + wg * 5120) & 0x3FFFF) >> 4) | ((uint64_t)8 << 32);
    wgmma_fence();
    wgmma_n192<0, 0>(acc[1], de + 64, de + 128, 1);
    wgmma_commit();
    wgmma_n192<0, 0>(acc[0], de, de + 128, 1);
  }
  TAIL(so0);
  TAIL(so1);
  const int cta = opaque_cta(), tid = opaque_tid(), lane = tid & 31, g = lane >> 2, t = lane & 3;
  const int wq = __shfl_sync(0xffffffffu, (tid >> 5) & 3, 0), hf = wq & 1;
  const int T = wg * 8 + (cta & 7), tn = cta >> 3;
  uint4* const hp = &g_halo[(T * 16 + tn) * 256 + (wq >> 1) * 128 + lane];
  uint32_t Q[2][8][2], K[2][8][2], V[2][8][2];
#define PACKKV(b)                                                                                       \
  _Pragma("unroll") for (int jj = 7; jj >= 0; jj--) {                                                   \
    V[b][jj][1] = movmatrix_t(PK(b, jj + 16, 1)); V[b][jj][0] = PK(b, jj + 16, 0);                      \
  }                                                                                                     \
  _Pragma("unroll") for (int jj = 7; jj >= 0; jj--) { K[b][jj][1] = PK(b, jj + 8, 1); K[b][jj][0] = PK(b, jj + 8, 0); }
#define PACKQ(b)                                                                                        \
  _Pragma("unroll") for (int jj = 7; jj >= 0; jj--) {                                                   \
    V[b][jj][0] = movmatrix_t(V[b][jj][0]); Q[b][jj][1] = PK(b, jj, 1); Q[b][jj][0] = PK(b, jj, 0);     \
  }
#define HALO_OUT(b, a)                                                                                  \
  sts128(a, make_uint4(K[b][0][1], K[b][1][1], K[b][2][1], K[b][3][1]));                                \
  sts128(a + 512, make_uint4(K[b][4][1], K[b][5][1], K[b][6][1], K[b][7][1]));                          \
  sts128(a + 1024, make_uint4(V[b][0][1], V[b][1][1], V[b][2][1], V[b][3][1]));                         \
  sts128(a + 1536, make_uint4(V[b][4][1], V[b][5][1], V[b][6][1], V[b][7][1]))
  wgmma_wait<2>();
  PIN(1, 0, 96);
  TRE(wg, l * 32 + 1);
  PACKKV(1);
  if (!hf) { HALO_OUT(1, slot0 + (5 + wq) * 2048 + lane * 16); }
  else if (T < 15) {
#pragma unroll
    for (int i = 0; i < 2; i++) {
      __stcg(hp + i * 32, make_uint4(~K[1][i * 4][1], ~K[1][i * 4 + 1][1], ~K[1][i * 4 + 2][1], ~K[1][i * 4 + 3][1]));
      __stcg(hp + (i + 2) * 32, make_uint4(~V[1][i * 4][1], ~V[1][i * 4 + 1][1], ~V[1][i * 4 + 2][1], ~V[1][i * 4 + 3][1]));
    }
  }
  TRE(wg, l * 32 + 2);
  wgmma_fence();
  TAIL(so2);
  wgmma_wait<2>();
  if ((tid & 127) == 0) mbar_arrive_n(EB(0), 2);
  PACKQ(1);
  wgmma_wait<1>();
  if ((r >> 19) & 15) bar_arrive((r >> 19) & 15, 256);
  if ((tid & 127) == 0) mbar_arrive_n(EB(NT - 2), 2);
  const bool o0 = 2 * t > g, o1 = 2 * t + 1 > g;
  float rk[2][4], rq[2][4];
#pragma unroll
  for (int b = 0; b < 2; b++) {
    const uint32_t a = sbase + OFF_ST + ((wq >> 1) * 72 + 8 + b * 32 + hf * 16) * 4;
    const float kscale = 0.17677669529663687f * 1.4426950408889634f;
    const float q0 = __uint_as_float(lds32(a + g * 4)) * kscale, q1 = __uint_as_float(lds32(a + g * 4 + 32)) * kscale;
    const uint32_t a0 = a + t * 8 - (o0 ? 32 : 0), a1 = a + t * 8 + 4 - (o1 ? 32 : 0);
    rk[b][0] = __uint_as_float(lds32(a0)); rk[b][1] = __uint_as_float(lds32(a1));
    rk[b][2] = __uint_as_float(lds32(a0 + 32)); rk[b][3] = __uint_as_float(lds32(a1 + 32));
    rq[b][0] = rk[b][0] * q0; rq[b][1] = rk[b][1] * q0; rq[b][2] = rk[b][2] * q1; rq[b][3] = rk[b][3] * q1;
  }
  const bool remote = !hf && T > 0 && !SKEL;
  uint4 hv[4];
#pragma unroll
  for (int i = 0; i < 4; i++)
    asm volatile("{\n.reg .pred p;\nsetp.ne.u32 p, %5, 0;\nmov.u32 %0, -1;\nmov.u32 %1, -1;\nmov.u32 %2, -1;\nmov.u32 %3, -1;\n"
                 "@p ld.relaxed.gpu.global.v4.u32 {%0,%1,%2,%3}, [%4];\n}\n"
                 : "=&r"(hv[i].x), "=&r"(hv[i].y), "=&r"(hv[i].z), "=&r"(hv[i].w) : "l"(hp - 16 * 256 + i * 32), "r"((int)remote) : "memory");
  wgmma_wait<0>();
  PIN(0, 0, 96);
  if ((tid & 127) == 0) mbar_arrive_n(EB(NT - 1), 2);
  TRC(wg, c.ri, 3);
  c.ri++;
  PACKKV(0);
  HALO_OUT(0, slot0 + (hf ? 3 + wq : 2 + (wq >> 1)) * 2048 + lane * 16);
  PACKQ(0);
  TRE(wg, l * 32 + 29);
  bar_sync(7 + wg, 128);
  uint32_t HK[2][8], HV[2][8];
#pragma unroll
  for (int b = 1; b >= 0; b--) {
    if (b == 1 || hf) {
      const uint32_t a = slot0 + (b ? 4 + wq : 2 + (wq >> 1)) * 2048 + lane * 16;
      const uint4 k0 = lds128(a), k1 = lds128(a + 512), v0 = lds128(a + 1024), v1 = lds128(a + 1536);
      HK[b][0] = k0.x; HK[b][1] = k0.y; HK[b][2] = k0.z; HK[b][3] = k0.w; HK[b][4] = k1.x; HK[b][5] = k1.y; HK[b][6] = k1.z; HK[b][7] = k1.w;
      HV[b][0] = v0.x; HV[b][1] = v0.y; HV[b][2] = v0.z; HV[b][3] = v0.w; HV[b][4] = v1.x; HV[b][5] = v1.y; HV[b][6] = v1.z; HV[b][7] = v1.w;
    } else {
#pragma unroll 1
      for (int it = 0; it < (1 << 20); it++) {
        uint32_t mn = ~0u;
#pragma unroll
        for (int i = 0; i < 4; i++) mn = min(min(mn, min(hv[i].x, hv[i].y)), min(hv[i].z, hv[i].w));
        if (__all_sync(0xffffffffu, mn != 0)) break;
        __nanosleep(HALO_NS);
#pragma unroll
        for (int i = 0; i < 4; i++) hv[i] = ld_volatile4(hp - 16 * 256 + i * 32);
      }
#pragma unroll
      for (int i = 0; i < 2; i++) {
        HK[0][i * 4] = ~hv[i].x; HK[0][i * 4 + 1] = ~hv[i].y; HK[0][i * 4 + 2] = ~hv[i].z; HK[0][i * 4 + 3] = ~hv[i].w;
        HV[0][i * 4] = ~hv[i + 2].x; HV[0][i * 4 + 1] = ~hv[i + 2].y; HV[0][i * 4 + 2] = ~hv[i + 2].z; HV[0][i * 4 + 3] = ~hv[i + 2].w;
      }
    }
  }
  TRE(wg, l * 32 + 3);
  float S[2][2][3][4];
#pragma unroll
  for (int b = 1; b >= 0; b--)
#pragma unroll
    for (int u = 0; u < 2; u++)
#pragma unroll
      for (int kt = 0; kt < 3; kt++) S[b][u][kt][0] = S[b][u][kt][1] = S[b][u][kt][2] = S[b][u][kt][3] = 0.f;
#pragma unroll
  for (int ks = 0; ks < 2; ks++)
#pragma unroll
    for (int b = 1; b >= 0; b--)
#pragma unroll
      for (int u = 0; u < 2; u++) {
        const int j0 = u * 4 + ks * 2;
        mma16816(S[b][u][1], Q[b][j0][0], Q[b][j0][1], Q[b][j0 + 1][0], Q[b][j0 + 1][1], K[b][j0][0], K[b][j0 + 1][0]);
        mma16816(S[b][u][2], Q[b][j0][0], Q[b][j0][1], Q[b][j0 + 1][0], Q[b][j0 + 1][1], K[b][j0][1], K[b][j0 + 1][1]);
        mma16816(S[b][u][0], Q[b][j0][0], Q[b][j0][1], Q[b][j0 + 1][0], Q[b][j0 + 1][1], HK[b][j0], HK[b][j0 + 1]);
      }
  TRE(wg, l * 32 + 4);
  const uint32_t mold = (o0 ? 0xffffu : 0u) | (o1 ? 0xffff0000u : 0u);
  const float NEG = -3.0e38f;
  const bool first = T == 0 && !hf;
  uint32_t pl[2][2], ph[2][2];
#pragma unroll
  for (int b = 1; b >= 0; b--)
#pragma unroll
    for (int u = 0; u < 2; u++) {
      float a0 = (o0 ? S[b][u][0][0] : S[b][u][1][0]) * rq[b][0], a1 = (o1 ? S[b][u][0][1] : S[b][u][1][1]) * rq[b][1];
      float b0 = (o0 ? S[b][u][1][2] : S[b][u][2][2]) * rq[b][2], b1 = (o1 ? S[b][u][1][3] : S[b][u][2][3]) * rq[b][3];
      if (b == 0) { a0 = (first && o0) ? NEG : a0; a1 = (first && o1) ? NEG : a1; }
      float m0 = fmaxf(a0, a1), m1 = fmaxf(b0, b1);
      m0 = fmaxf(m0, __shfl_xor_sync(0xffffffffu, m0, 1)); m1 = fmaxf(m1, __shfl_xor_sync(0xffffffffu, m1, 1));
      m0 = fmaxf(m0, __shfl_xor_sync(0xffffffffu, m0, 2)); m1 = fmaxf(m1, __shfl_xor_sync(0xffffffffu, m1, 2));
      a0 = ex2_fast(a0 - m0); a1 = ex2_fast(a1 - m0); b0 = ex2_fast(b0 - m1); b1 = ex2_fast(b1 - m1);
      float s0 = a0 + a1, s1 = b0 + b1;
      s0 += __shfl_xor_sync(0xffffffffu, s0, 1); s1 += __shfl_xor_sync(0xffffffffu, s1, 1);
      s0 += __shfl_xor_sync(0xffffffffu, s0, 2); s1 += __shfl_xor_sync(0xffffffffu, s1, 2);
      s0 = rcp_fast(s0); s1 = rcp_fast(s1);
      pl[b][u] = pack2(a0 * rk[b][0] * s0, a1 * rk[b][1] * s0); ph[b][u] = pack2(b0 * rk[b][2] * s1, b1 * rk[b][3] * s1);
    }
  float O[2][2][4][4];
#pragma unroll
  for (int b = 1; b >= 0; b--)
#pragma unroll
    for (int u = 0; u < 2; u++)
#pragma unroll
      for (int nt = 0; nt < 4; nt++) {
        O[b][u][nt][0] = O[b][u][nt][1] = O[b][u][nt][2] = O[b][u][nt][3] = 0.f;
        mma1688(O[b][u][nt], pl[b][u] & ~mold, ph[b][u] & mold, V[b][u * 4 + nt][0]);
      }
#pragma unroll
  for (int b = 1; b >= 0; b--)
#pragma unroll
    for (int u = 0; u < 2; u++)
#pragma unroll
      for (int nt = 0; nt < 4; nt++) mma1688(O[b][u][nt], 0u, ph[b][u] & ~mold, V[b][u * 4 + nt][1]);
#pragma unroll
  for (int b = 1; b >= 0; b--)
#pragma unroll
    for (int u = 0; u < 2; u++)
#pragma unroll
      for (int nt = 0; nt < 4; nt++) mma1688(O[b][u][nt], pl[b][u] & mold, 0u, HV[b][u * 4 + nt]);
  {
    uint32_t dep = 0;
#pragma unroll
    for (int i = 0; i < 16; i++) dep |= __float_as_uint(O[i >> 3][(i >> 2) & 1][i & 3][0]);
    bar_arrive(3 + wg + (dep & lds32(sbase + OFF_K01 + 4)), 256);
  }
  TRE(wg, l * 32 + 5);
  bf16* op = g_o + (size_t)(T * 128 + (hf * 16 + g) * 2 + (wq >> 1)) * D_DIM + tn * 64 + t * 8;
#pragma unroll
  for (int b = 1; b >= 0; b--)
#pragma unroll
    for (int u = 0; u < 2; u++)
#pragma unroll
      for (int h = 0; h < 2; h++)
        stg128(op + (b * 64 + h * 16) * D_DIM + u * 32, pack2(O[b][u][0][h * 2], O[b][u][0][h * 2 + 1]), pack2(O[b][u][1][h * 2], O[b][u][1][h * 2 + 1]),
               pack2(O[b][u][2][h * 2], O[b][u][2][h * 2 + 1]), pack2(O[b][u][3][h * 2], O[b][u][3][h * 2 + 1]));
  __syncwarp();
  e_arrive(sbase + OFF_OST + wg * 8);
  if (remote) {
#pragma unroll
    for (int i = 0; i < 4; i++) __stcg(hp - 16 * 256 + i * 32, make_uint4(0, 0, 0, 0));
  }
  TRE(wg, l * 32 + 6);
}

__device__ __forceinline__ uint4 ext_row(float mean) {
  const uint32_t hi = pack2(mean, mean);
  return make_uint4(hi, pack2(mean - bf_lo(hi), 0.f), 0, 0);
}
__device__ __forceinline__ uint4 ext_col(float cs) {
  cs *= -0.5f;
  const float hi = bf_lo(pack2(cs, 0.f));
  return make_uint4(pack2(hi, cs - hi), pack2(hi, 0.f), 0, 0);
}

__device__ __forceinline__ void init_down(float (&acc)[1][64], const uint32_t (&xr)[32], uint32_t sbase) {
  const int tid = opaque_tid();
  uint16_t bb0, bb1;
  const uint32_t ba = sbase + OFF_B2 + ((tid >> 5) * 16 + ((tid & 31) >> 2)) * 2;
  asm volatile("ld.shared.u16 %0, [%1];" : "=h"(bb0) : "r"(ba) : "memory");
  asm volatile("ld.shared.u16 %0, [%1];" : "=h"(bb1) : "r"(ba + 16) : "memory");
  const float k = 2.f * GELU_C, bias0 = __uint_as_float((uint32_t)bb0 << 16) * k, bias1 = __uint_as_float((uint32_t)bb1 << 16) * k;
#pragma unroll
  for (int j = 0; j < 16; j++) {
    acc[0][j * 4 + 0] = fmaf(bf_lo(xr[j * 2]), k, bias0); acc[0][j * 4 + 1] = fmaf(bf_hi(xr[j * 2]), k, bias0);
    acc[0][j * 4 + 2] = fmaf(bf_lo(xr[j * 2 + 1]), k, bias1); acc[0][j * 4 + 3] = fmaf(bf_hi(xr[j * 2 + 1]), k, bias1);
  }
}
template <int W>
__device__ __forceinline__ void mixer_up(const Params& P, uint32_t sbase, Cons& c, int l, float (&acc4)[1][64], const uint32_t (&xr)[32],
                                         const uint32_t (&bw)[24]) {
  constexpr int MW = 2 - W, BN = W ? 192 : 128;
  float acc[MW][BN / 2];
  {
#pragma unroll
    for (int j = 0; j < BN / 8; j++) {
      uint32_t bv;
      asm volatile("mov.b32 %0, %1;" : "=r"(bv) : "r"(bw[j]));
      const float b0 = bf_lo(bv) * GELU_C, b1 = bf_hi(bv) * GELU_C;
#pragma unroll
      for (int b = 0; b < MW; b++) { acc[b][j * 4 + 0] = acc[b][j * 4 + 2] = b0; acc[b][j * 4 + 1] = acc[b][j * 4 + 3] = b1; }
    }
  }
  gemm_runs<MW, BN, 1, 1, 4, 4, 0, MW * 8192, 0, 0, 1>(P, sbase, c, acc, W);
  TRE(W, l * 32 + 16);
  if (W) init_down(acc4, xr, sbase);
  const int cta = opaque_cta(), tid = opaque_tid(), lane = tid & 31;
  bf16* up = g_u + (size_t)((cta & 7) * 128 + (W ? (cta & 8) * 8 : 0) + ((tid >> 5) & 3) * 16 + (lane >> 2)) * F_DIM +
             (W ? 2048 + (cta >> 4) * 192 : (cta >> 3) * 128) + (lane & 3) * 8;
  float k01 = GELU_B, knext = GELU_B;
  const uint32_t r = P.run[W][c.ri];
  uint32_t so = ((r >> 6) & 31) * 512, e8 = (r >> 8) & 0x38;
  const uint64_t da0 = make_desc(sbase + 16384 + 8192, 8192, 1024), db0 = make_desc(sbase, 16, 1024);
  if (W) { TRC(W, c.ri, 0); }
#pragma unroll
  for (int j = 0; j < 8 - W * 2; j++) {
    if (j == 4 && !W) {
      __syncwarp();
      e_arrive(sbase + OFF_TU0);
    }
    if (W) {
      mbar_wait(sbase + OFF_FULL + 128 + (c.nshr & 7) * 8, (c.nshr >> 3) & 1);
      if (j == 0) { TRC(W, c.ri, 2); }
      c.nshr++;
      wgmma_fence();
#pragma unroll
      for (int k = 0; k < 4; k++) WG<128, 1, 0>::mma(acc4[0], da0 + so + k * 128, db0 + so + k * 2);
      wgmma_commit();
      so = so > (RING_LIM((r >> 25) & 3) - 8) * 512 ? 0 : so + 4 * 512;
      if (j) {
        wgmma_wait<1>();
        if ((tid & 127) == 0) mbar_arrive(sbase + OFF_EMPTY + e8);
        e8 = (e8 + 8) & 0x38;
      }
    }
    if (!W && j >= 4) __nanosleep(j == 4 ? P.u0d : P.u1d);
    if (W || j >= 4) k01 = __uint_as_float(lds32(sbase + OFF_K01));
    else k01 = knext;
    if (!W && j < 3) knext = __uint_as_float(lds32(sbase + OFF_K01));
    const int gr = W ? j : j >> 1, mb = W ? 0 : j & 1;
#pragma unroll
    for (int h = 0; h < 2; h++) {
      const float* v = &acc[mb][gr * 16 + h * 2];
      stg128(up + (mb * 64 + h * 8) * F_DIM + gr * 32, pack2(gelu_tanh(v[0], k01), gelu_tanh(v[1], k01)), pack2(gelu_tanh(v[4], k01), gelu_tanh(v[5], k01)),
             pack2(gelu_tanh(v[8], k01), gelu_tanh(v[9], k01)), pack2(gelu_tanh(v[12], k01), gelu_tanh(v[13], k01)));
    }
  }
  __syncwarp();
  e_arrive(sbase + OFF_TU1 + W * 8);
  TRE(W, l * 32 + 17);
  if (W) {
    wgmma_wait<0>();
    if ((tid & 127) == 0) mbar_arrive(sbase + OFF_EMPTY + e8);
#pragma unroll
    for (int i = 0; i < 64; i++) asm volatile("" : "+f"(acc4[0][i])::"memory");
    TRC(W, c.ri, 3);
    c.ri++;
  } else init_down(acc4, xr, sbase);
}

__device__ __forceinline__ void row_stats(const uint4 (&raw)[8], int row0, unsigned tag, int lane) {
  float s[2], q[2];
#pragma unroll
  for (int rr = 0; rr < 2; rr++) {
    s[rr] = 0.f; q[rr] = 0.f;
#pragma unroll
    for (int i = 0; i < 4; i++) {
      float v[8];
      unpack8(raw[rr * 4 + i], v);
      s[rr] += ((v[0] + v[1]) + (v[2] + v[3])) + ((v[4] + v[5]) + (v[6] + v[7]));
#pragma unroll
      for (int e = 0; e < 8; e++) q[rr] = fmaf(v[e], v[e], q[rr]);
    }
  }
#pragma unroll
  for (int o = 16; o > 0; o >>= 1)
#pragma unroll
    for (int rr = 0; rr < 2; rr++) { s[rr] += __shfl_xor_sync(0xffffffffu, s[rr], o); q[rr] += __shfl_xor_sync(0xffffffffu, q[rr], o); }
  const int row = row0 + (lane & 1);
  if (lane < 16)
    __stcg(&g_statsA[((row >> 6) * 8 + (lane >> 1)) * 64 + (row & 63)],
           make_uint4(__float_as_uint(((lane & 1) ? s[1] : s[0]) * 0.125f), tag, __float_as_uint(((lane & 1) ? q[1] : q[0]) * 0.125f), tag));
}
__device__ __forceinline__ uint4 ldg_v(const uint4* p) {
  uint4 v;
  asm volatile("ld.global.nc.v4.u32 {%0,%1,%2,%3}, [%4];" : "=r"(v.x), "=r"(v.y), "=r"(v.z), "=r"(v.w) : "l"(p) : "memory");
  return v;
}
__device__ __noinline__ void startup(const bf16* __restrict__ x, const bf16* __restrict__ wqkv, const bf16* __restrict__ b1,
                                     const bf16* __restrict__ b2, uint32_t sbase, unsigned tag, unsigned delay) {
  const int cta = LCTA, lane = threadIdx.x & 31, wq = __shfl_sync(0xffffffffu, (threadIdx.x >> 5) & 3, 0), m = cta >> 3, j = cta & 7;
  const int i = threadIdx.x & 127, row0 = cta * 8 + wq * 2;
  __nanosleep(delay);
  const uint4* xs = reinterpret_cast<const uint4*>(x + (size_t)row0 * D_DIM) + lane;
  const uint4* ws = reinterpret_cast<const uint4*>(wqkv + (size_t)(j * 128 + wq * 32 + (lane >> 3)) * (3 * D_DIM) + m * 64) + (lane & 7);
  uint4 raw[8], wr[8];
#pragma unroll
  for (int k = 0; k < 8; k++) raw[k] = ldg_v(xs + k * 32);
#pragma unroll
  for (int k = 0; k < 8; k++) wr[k] = ldg_v(ws + k * 4 * 384);
  if (wq < 3) __stcg(&g_cs[j * 1536 + m * 96 + i], make_uint4(0, 0, 0, 0));
  if (i < 40) {
    const uint4 v = *reinterpret_cast<const uint4*>(b1 + (i < 16 ? m * 128 : 1920 + (m >> 1) * 192) + i * 8);
    const uint32_t a = sbase + OFF_B1 + (i < 16 ? i * 4 : 320 + i * 4);
    sts32(a, v.x); sts32(a + 96, v.y); sts32(a + 192, v.z); sts32(a + 288, v.w);
  }
  if (i >= 64 && i < 80) sts128(sbase + OFF_B2 + (i - 64) * 16, *reinterpret_cast<const uint4*>(b2 + (((i >> 3) & 1) * 16 + m) * 64 + (i & 7) * 8));
  const uint32_t sa = sbase + OFF_HALO;
#define WAITFOR(v) if (v[7].x == tag + v[7].y * 65536 + 12345 && v[6].w == 99) delay++
#define COLSUM(v, p)                                                                                                          \
  {                                                                                                                           \
    float s[8];                                                                                                               \
    _Pragma("unroll") for (int e = 0; e < 8; e++) s[e] = 0.f;                                                                 \
    _Pragma("unroll") for (int k = 0; k < 8; k++) {                                                                           \
      float f[8];                                                                                                             \
      unpack8(v[k], f);                                                                                                       \
      _Pragma("unroll") for (int e = 0; e < 8; e++) s[e] += f[e];                                                             \
    }                                                                                                                         \
    const uint32_t a = sa + (wq * 4 + (lane >> 3)) * 768 + (p) * 256 + (lane & 7) * 32;                                       \
    sts128(a, make_uint4(__float_as_uint(s[0]), __float_as_uint(s[1]), __float_as_uint(s[2]), __float_as_uint(s[3])));       \
    sts128(a + 16, make_uint4(__float_as_uint(s[4]), __float_as_uint(s[5]), __float_as_uint(s[6]), __float_as_uint(s[7])));  \
  }
  uint4 w2[8];
  WAITFOR(raw);
#pragma unroll
  for (int k = 0; k < 8; k++) w2[k] = ldg_v(ws + 128 + k * 4 * 384 + (delay >> 31));
  row_stats(raw, row0, tag, lane);
  WAITFOR(wr);
#pragma unroll
  for (int k = 0; k < 8; k++) raw[k] = ldg_v(ws + 256 + k * 4 * 384 + (delay >> 31));
  COLSUM(wr, 0);
  COLSUM(w2, 1);
  COLSUM(raw, 2);
  bar_sync(8, 128);
  if (wq < 3) {
    float a = 0.f, b = 0.f;
#pragma unroll
    for (int r = 0; r < 16; r++) { const float2 v = lds64f(sa + r * 768 + i * 8); a += v.x; b += v.y; }
    __stcg(&g_cs[j * 1536 + m * 96 + i], make_uint4(__float_as_uint(a), tag, __float_as_uint(b), tag));
  }
  TRE(1, 24);
#pragma unroll
  for (int k = 0; k < 8; k++) raw[k] = ldg_v(xs + 1024 * 128 + k * 32);
#pragma unroll 1
  for (int q = wq == 3 ? 0 : 1; q < 2; q++) {
    const int tk = q ? i : lane - 32;
    const int row = max(j * 128 + tk, 0);
    const uint4* p = &g_statsA[(row >> 6) * 512 + (row & 63)];
    uint4 v;
#pragma unroll 1
    for (int it = 0; it < (1 << 20); it++) {
      v = ld_volatile4(p);
      if (__all_sync(0xffffffffu, v.y == tag && v.w == tag)) break;
      __nanosleep(200);
    }
    const float mean = __uint_as_float(v.x) * (8.0f / D_DIM);
    const float rs = rsqrtf(fmaxf(fmaf(__uint_as_float(v.z), 8.0f / D_DIM, -mean * mean), 0.f) + 1e-5f);
    if (tk >= -16) sts32(sbase + OFF_ST + ((tk & 1) * 72 + 8 + (tk >> 1)) * 4, __float_as_uint(rs));
    if (q) sts128(sbase + OFF_EXT + ((i & 64) + (i & 1) * 32 + ((i & 63) >> 1)) * 16, ext_row(mean));
  }
  if (wq < 3) {
    const uint4* p = &g_cs[m * 96 + i];
    uint4 v[8];
#pragma unroll 1
    for (int it = 0; it < (1 << 20); it++) {
      bool ok = true;
#pragma unroll
      for (int r = 0; r < 8; r++) v[r] = ld_volatile4(p + r * 1536);
#pragma unroll
      for (int r = 0; r < 8; r++) ok = ok && v[r].y == tag && v[r].w == tag;
      if (__all_sync(0xffffffffu, ok)) break;
      __nanosleep(100);
    }
    float a = 0.f, b = 0.f;
#pragma unroll
    for (int r = 0; r < 8; r++) { a += __uint_as_float(v[r].x); b += __uint_as_float(v[r].z); }
    sts64f(sbase + OFF_CS + i * 8, a, b);
    sts128(sbase + OFF_EXT + 2048 + i * 32, ext_col(a));
    sts128(sbase + OFF_EXT + 2048 + i * 32 + 16, ext_col(b));
  }
  if (i == 0) sts32(sbase + OFF_SFR, tag);
  fence_proxy_async_smem();
  bar_sync(8, 128);
  if (i == 0) mbar_arrive(sbase + OFF_STR);
  TRE(1, 27);
  row_stats(raw, row0 + 1024, tag, lane);
  __syncwarp();
}

__device__ __forceinline__ void poll8(uint4 (&v)[8], const uint4* p, int stride, unsigned tag) {
#pragma unroll 1
  for (int it = 0; it < (1 << 20); it++) {
    bool ok = true;
#pragma unroll
    for (int i = 0; i < 8; i++) v[i] = ld_volatile4(p + i * stride);
#pragma unroll
    for (int i = 0; i < 8; i++) ok = ok && v[i].y == tag && v[i].w == tag;
    if (SKEL || __all_sync(0xffffffffu, ok)) break;
    __nanosleep(200);
  }
}

__global__ void __launch_bounds__(384, 1)
mega_kernel(const __grid_constant__ Params P, const bf16* __restrict__ x, const bf16* __restrict__ wqkv, const bf16* __restrict__ b1,
            const bf16* __restrict__ b2, bf16* __restrict__ out) {
  extern __shared__ __align__(1024) uint8_t smem_raw[];
  const uint32_t sbase = smem_u32(smem_raw);
  if (threadIdx.x < PFK * 32 && blockIdx.x < 128) {
    const int i = blockIdx.x * 32 + (threadIdx.x & 31), k = threadIdx.x >> 5;
    const bf16* p = i < 1024 ? x + (size_t)i * D_DIM + k * 64 : wqkv + (size_t)k * 64 * 3 * D_DIM + (i - 1024) * 64;
    asm volatile("prefetch.global.L2 [%0];" ::"l"(p));
  }
  {
    const int wi = __shfl_sync(0xffffffffu, threadIdx.x >> 5, 0);
    if (wi == 4) {
      uint32_t id, nsm;
      asm volatile("mov.u32 %0, %smid;" : "=r"(id));
      asm volatile("mov.u32 %0, %nsmid;" : "=r"(nsm));
      const bool bysm = gridDim.x == 132 && nsm == 132;
      id = __shfl_sync(0xffffffffu, bysm ? id : blockIdx.x, 0);
      const int lcta = P.pair[bysm][id >> 1] + (id & 1);
      if ((threadIdx.x & 31) == 0) {
#pragma unroll
        for (int s = 0; s < 8; s++) mbar_init(sbase + OFF_FULL + s * 8, 2);
        asm volatile("fence.mbarrier_init.release.cluster;" ::: "memory");
      }
      sts128(sbase + OFF_K01, make_uint4(__float_as_uint(GELU_B), 0, lcta, 0x3f800000));
      __syncwarp();
      bar_arrive(0, 384);
      if (lcta >= 0) {
#pragma unroll 1
        for (int e = 0; e < 5; e++) {
          const uint32_t fb = sbase + OFF_FULL + e * 8;
          e_tma_load(sbase + e * 40960, &P.xq[0], fb, e * 64, 0, (lcta & 7) * 2, 0, POL_NORMAL);
          e_tma_load(sbase + e * 40960 + 16384, &P.wqkv, fb, (lcta >> 3) * 64, e * 64, 0, 0, POL_NORMAL);
          e_expect_tx(fb, 40960);
          e_arrive(fb);
          if (e >= PFK - 1) __nanosleep(P.ild);
        }
      }
    } else {
      if (wi >= 5 && wi < 11 && (threadIdx.x & 31) == 0) {
      const uint32_t a = sbase + (wi < 9 ? OFF_FULL + (wi - 4) * 64 : wi == 9 ? OFF_TU1 : OFF_DEP + 16);
      const uint32_t c0 = wi < 8 ? 2 : wi == 9 ? 4 : 1, c1 = wi < 8 ? 2 : wi == 8 ? 4 : 1;
      mbar_init(a, c0); mbar_init(a + 8, c0);
      if (wi == 9) { mbar_init(sbase + OFF_DEP, 1); mbar_init(sbase + OFF_DEP + 8, 1); }
      else {
#pragma unroll
        for (int s = 2; s < 8; s++) mbar_init(a + s * 8, c1);
      }
      asm volatile("fence.mbarrier_init.release.cluster;" ::: "memory");
      }
      __syncwarp();
      bar_sync(0, 384);
    }
  }

  if (LCTA < 0) {
    if (threadIdx.x == 0) {
      const unsigned epoch = EPOCH();
#pragma unroll 1
      for (int it = 0; it < (1 << 20) && (int)(*(volatile unsigned*)&g_sync[0] - (epoch * 16 + 1) * NCTA) < 0; it++) __nanosleep(2000);
    }
    return;
  }
  const int warp = __shfl_sync(0xffffffffu, threadIdx.x >> 5, 0);
  const int wg = warp >> 2;
  if (__shfl_sync(0xffffffffu, threadIdx.x >> 8, 0) == 0) {
    asm volatile("setmaxnreg.inc.sync.aligned.u32 %0;" ::"n"(RHI));
    if (wg == 1) startup(x, wqkv, b1, b2, sbase, EPOCH() * 2 + 1, P.sud);
    Cons c;
    c.nsolo = 0; c.nshr = 0; c.ri = 0;
    float acc4[1][64];
#pragma unroll
    for (int i = 0; i < 64; i++) acc4[0][i] = 0.f;
#pragma unroll 1
    for (int l = -1;; l++) {
      if (l >= 0) {
        uint32_t pk[32];
        gemm_runs<1, 128, 1, 0, 3, 4, 16384, 0, 8192, 0, DP4>(P, sbase, c, acc4, wg);
        TRE(wg, l * 32 + 20);
#pragma unroll
        for (int i = 0; i < 64; i++) acc4[0][i] *= 0.5f / GELU_C;
        const int cta = opaque_cta(), tid = opaque_tid(), lane = tid & 31, rw = ((tid >> 5) & 3) * 16;
#pragma unroll
        for (int j = 0; j < 16; j++) {
          pk[j * 2] = pack2(acc4[0][j * 4 + 0], acc4[0][j * 4 + 1]);
          pk[j * 2 + 1] = pack2(acc4[0][j * 4 + 2], acc4[0][j * 4 + 3]);
        }
        store_tile128(pk, (l ? out : g_x2) + (size_t)((wg * 16 + (cta >> 3)) * 64 + rw + (lane >> 2)) * D_DIM + (cta & 7) * 128 + (lane & 3) * 8,
                      sbase + OFF_TR + wg * 8, lane);
        TRE(wg, l * 32 + 21);
        if (l == 0) tile_stats<true>(acc4[0], &g_statsA[(wg * 16 + (cta >> 3)) * 512 + (cta & 7) * 64 + rw + (lane >> 2)], lds32(sbase + OFF_SFR) + 1, lane & 3,
                               __uint_as_float(lds32(sbase + OFF_K01 + 4)));
        TRE(wg, l * 32 + 22);
        if (l) break;
      }
      l++;
      {
        float acc[2][96];
#pragma unroll
        for (int b = 0; b < 2; b++)
#pragma unroll
          for (int i = 0; i < 96; i++) acc[b][i] = 0.f;
        gemm_runs<2, 192, 0, 1, 5, 5, 0, 16384, 0, 0, 1>(P, sbase, c, acc, wg);
        attention(P, acc, sbase, c, wg, l);
      }
      uint32_t bw[24];
      uint32_t xr[32];
      {
        float acc[1][64];
        {
          if (PREW) {
            const int cta = opaque_cta(), tid = opaque_tid();
            if ((tid & 3) < 2) __stcg(&g_statsB[(wg * 16 + (cta >> 3)) * 512 + (cta & 7) * 64 + ((tid >> 5) & 3) * 16 + ((tid & 31) >> 2) + (tid & 3) * 8], make_uint4(0, 0, 0, 0));
          }
          const int cta = opaque_cta(), tid = opaque_tid();
          const uint4* rp = reinterpret_cast<const uint4*>((l ? g_x2 : x) + (size_t)((wg * 16 + (cta >> 3)) * 64 + ((tid >> 5) & 3) * 16 + ((tid & 31) >> 2)) * D_DIM +
                                                           (cta & 7) * 128) + (tid & 3);
          __nanosleep(P.rsd);
          uint4 q[8];
#pragma unroll
          for (int i = 0; i < 8; i++) q[i] = __ldcg(rp + (i & 1) * D_DIM + (i >> 1) * 4);
#pragma unroll
          for (int i = 0; i < 8; i++) {
            quad_transpose(q[i].x, q[i].y, q[i].z, q[i].w, tid & 3);
            float* a = &acc[0][(i >> 1) * 16 + (i & 1) * 2];
            a[0] = bf_lo(q[i].x); a[1] = bf_hi(q[i].x); a[4] = bf_lo(q[i].y); a[5] = bf_hi(q[i].y);
            a[8] = bf_lo(q[i].z); a[9] = bf_hi(q[i].z); a[12] = bf_lo(q[i].w); a[13] = bf_hi(q[i].w);
          }
        }
        gemm_runs<1, 128, 0, 1, 3, 3, 16384, 0, 0, 0, DP2>(P, sbase, c, acc, wg);
        TRE(wg, l * 32 + 10);
        const int cta = opaque_cta(), tid = opaque_tid(), lane = tid & 31, rw = ((tid >> 5) & 3) * 16;
        const unsigned tag = lds32(sbase + OFF_SFR) + l;
        uint4* sb = &g_statsB[(wg * 16 + (cta >> 3)) * 512 + rw];
        tile_stats<false>(acc[0], sb + (cta & 7) * 64 + (lane >> 2), tag, lane & 3);
        TRE(wg, l * 32 + 11);
#pragma unroll
        for (int j = 0; j < 16; j++) {
          xr[j * 2] = pack2(acc[0][j * 4 + 0], acc[0][j * 4 + 1]);
          xr[j * 2 + 1] = pack2(acc[0][j * 4 + 2], acc[0][j * 4 + 3]);
        }
#define XTR(i) quad_transpose(xr[((i) >> 1) * 8 + ((i) & 1)], xr[((i) >> 1) * 8 + ((i) & 1) + 2], xr[((i) >> 1) * 8 + ((i) & 1) + 4], xr[((i) >> 1) * 8 + ((i) & 1) + 6], lane & 3)
        const uint4* sp = sb + (lane & 1) * 256 + (lane >> 1);
        __nanosleep(P.pre);
        uint4 a = ld_volatile4(sp), b = ld_volatile4(sp + 64), cc = ld_volatile4(sp + 128), d = ld_volatile4(sp + 192);
#pragma unroll
        for (int i = 0; i < 8; i++) XTR(i);
#pragma unroll
        for (int j = 0; j < 6; j++) {
          const uint4 v = lds128(sbase + OFF_B1 + wg * 384 + (lane & 3) * 96 + j * 16);
          bw[j * 4] = v.x; bw[j * 4 + 1] = v.y; bw[j * 4 + 2] = v.z; bw[j * 4 + 3] = v.w;
        }
#pragma unroll 1
        for (int it = 0; it < (1 << 20); it++) {
          const bool ok = a.y == tag && a.w == tag && b.y == tag && b.w == tag && cc.y == tag && cc.w == tag && d.y == tag && d.w == tag;
          if (SKEL || __all_sync(0xffffffffu, ok)) break;
          a = ld_volatile4(sp); b = ld_volatile4(sp + 64); cc = ld_volatile4(sp + 128); d = ld_volatile4(sp + 192);
        }
        __syncwarp();
        TRE(wg, l * 32 + 12);
        float mean = (__uint_as_float(a.x) + __uint_as_float(b.x)) + (__uint_as_float(cc.x) + __uint_as_float(d.x));
        float v = (__uint_as_float(a.z) + __uint_as_float(b.z)) + (__uint_as_float(cc.z) + __uint_as_float(d.z));
        mean += __shfl_xor_sync(0xffffffffu, mean, 1);
        v += __shfl_xor_sync(0xffffffffu, v, 1);
        mean *= (1.0f / D_DIM);
        v = fmaxf(fmaf(v, 1.0f / D_DIM, -mean * mean), 0.f);
        const float rs = GELU_C * rsqrtf(fmaf(v + 1e-5f, 1e-5f, v));
        mean *= -rs;
        const int g2 = (lane >> 2) * 2;
        const float nm0 = __shfl_sync(0xffffffffu, mean, g2), rs0 = __shfl_sync(0xffffffffu, rs, g2);
        const float nm1 = __shfl_sync(0xffffffffu, mean, g2 + 16), rs1 = __shfl_sync(0xffffffffu, rs, g2 + 16);
        uint32_t hk[32];
#pragma unroll
        for (int j = 0; j < 16; j++) {
          hk[j * 2] = pack2(fmaf(acc[0][j * 4 + 0], rs0, nm0), fmaf(acc[0][j * 4 + 1], rs0, nm0));
          hk[j * 2 + 1] = pack2(fmaf(acc[0][j * 4 + 2], rs1, nm1), fmaf(acc[0][j * 4 + 3], rs1, nm1));
        }
        store_tile128(hk, g_h + (size_t)((wg * 16 + (cta >> 3)) * 64 + rw + (lane >> 2)) * D_DIM + (cta & 7) * 128 + (lane & 3) * 8, sbase + OFF_TR + wg * 8, lane);
        TRE(wg, l * 32 + 13);
      }
      if (wg == 1) mixer_up<1>(P, sbase, c, l, acc4, xr, bw);
      else mixer_up<0>(P, sbase, c, l, acc4, xr, bw);
      l--;
    }
    TRE(wg, 62);
    TRG(wg, 62);
  } else {
    asm volatile("setmaxnreg.dec.sync.aligned.u32 %0;" ::"n"(RLO));
    if (warp < 10) {
      if (warp == 8) producer<0>(P, sbase);
      else producer<1>(P, sbase);
    } else {
      const unsigned epoch = __shfl_sync(0xffffffffu, EPOCH(), 0);
      const int cta = LCTA, w = warp - 10, j = cta & 7;
      unsigned* const cn = &g_sync[w];
      unsigned tgt = epoch << 11;
      if (w == 1 && (threadIdx.x & 31) < 11) prefetch_tmap(reinterpret_cast<const CUtensorMap*>(&P) + (threadIdx.x & 31));
      __syncwarp();
#pragma unroll 1
      for (int q9 = 0; q9 < 9; q9++) {
        const int l = q9 >= 5, q = q9 - l * 5;
        if (q == 0 && (w | l)) {
          const int lane = opaque_tid() & 31;
          const uint32_t half = sbase + OFF_EXT + (opaque_tid() & 32) * 160;
          mbar_wait(sbase + OFF_OST + 8 - w * 8, w ? l : 0);
#pragma unroll 1
          for (int r = 0; r < 6; r++) sts128(half + 2048 + (r * 32 + lane) * 16, ext_col(__uint_as_float(lds32(sbase + OFF_CS + (r * 32 + lane) * 4))));
#pragma unroll 1
          for (int t0 = -32; t0 < 128; t0 += 32) {
            float mean = 0.f, var = 0.f;
            {
              const int row = max((w * 8 + j) * 128 + t0 + lane, 0);
              uint4 v[8];
              poll8(v, &g_statsA[(row >> 6) * 512 + (row & 63)], 64, epoch * 2 + l + 1);
#pragma unroll
              for (int i = 0; i < 8; i++) { mean += __uint_as_float(v[i].x); var += __uint_as_float(v[i].z); }
            }
            const int tk = t0 + (opaque_tid() & 31);
            mean *= (1.0f / D_DIM);
            const float rs = rsqrtf(fmaxf(fmaf(var, 1.0f / D_DIM, -mean * mean), 0.f) + 1e-5f);
            if (tk >= -16) sts32(sbase + OFF_ST + ((tk & 1) * 72 + 8 + (tk >> 1)) * 4, __float_as_uint(rs));
            if (t0 >= 0) sts128(half + ((tk & 64) + (tk & 1) * 32 + ((tk & 63) >> 1)) * 16, ext_row(mean));
          }
          fence_proxy_async_smem();
          __syncwarp();
          e_arrive(sbase + OFF_STR + w * 8);
          TRA(w, l * 32 + 8);
        }
        if (w && q == 2) continue;
        mbar_wait(sbase + OFF_OST + (q == 4 ? 1 : q) * 16 + w * 8, q == 1 ? 0 : q == 4 ? 1 : l);
        TRA(w, l * 32 + ((0x1c001a0e07ull >> (q * 8)) & 31));
        const unsigned inc = q9 == 8 ? 8 + 2 * w : 1;
        e_red_release(cn, inc);
        TRA(w, l * 32 + ((0x1713120f09ull >> (q * 8)) & 31));
        spin_until(cn, tgt += inc * NCTA);
        e_arrive(sbase + OFF_DEP + (((0x86531 >> (q * 4)) & 15) + w) * 8);
      }
    }
  }
}

typedef CUresult (*PFN_encodeTiled)(CUtensorMap*, CUtensorMapDataType, cuuint32_t, void*, const cuuint64_t*,
                                    const cuuint64_t*, const cuuint32_t*, const cuuint32_t*, CUtensorMapInterleave,
                                    CUtensorMapSwizzle, CUtensorMapL2promotion, CUtensorMapFloatOOBfill);
static PFN_encodeTiled g_encode = nullptr;

static CUtensorMap make_map5(const void* ptr, int d0, int d1, int d2, int d3, int d4, int s1, int s2, int s3, int s4, int b1, int b2, int b3, int b4) {
  CUtensorMap m;
  cuuint64_t dims[5] = {(cuuint64_t)d0, (cuuint64_t)d1, (cuuint64_t)d2, (cuuint64_t)d3, (cuuint64_t)d4};
  cuuint64_t strides[4] = {(cuuint64_t)s1 * 2, (cuuint64_t)s2 * 2, (cuuint64_t)s3 * 2, (cuuint64_t)s4 * 2};
  cuuint32_t box[5] = {64, (cuuint32_t)b1, (cuuint32_t)b2, (cuuint32_t)b3, (cuuint32_t)b4};
  cuuint32_t es[5] = {1, 1, 1, 1, 1};
  g_encode(&m, CU_TENSOR_MAP_DATA_TYPE_BFLOAT16, 5, (void*)ptr, dims, strides, box, es, CU_TENSOR_MAP_INTERLEAVE_NONE,
           CU_TENSOR_MAP_SWIZZLE_128B, CU_TENSOR_MAP_L2_PROMOTION_L2_128B, CU_TENSOR_MAP_FLOAT_OOB_FILL_NONE);
  return m;
}
static CUtensorMap make_map(const void* ptr, int rows, int cols, int box_rows, int nblk = 1, int bstep = 64) {
  return make_map5(ptr, cols - (nblk - 1) * bstep, rows, nblk, 1, 1, cols, bstep, 64, 64, box_rows, nblk, 1, 1);
}
static CUtensorMap make_map_perm(const void* ptr, int rows, int cols) {
  return make_map5(ptr, cols, 2, 4, 4, rows / 32, cols, 8 * cols, 2 * cols, 32 * cols, 2, 4, 4, 2);
}

#define tune(n, d) (d)
#define PX tune("PX", 6)
#define PA1 tune("PA1", 1)
#define PY tune("PY", 8)
#define PB1 tune("PB1", 2)
#define PZ tune("PZ", 16)
#define PV tune("PV", 16)
#define PA4 tune("PA4", 12)

struct Sched {
  Params& P;
  int pos = 0, e = 0, nr[2] = {0, 0}, l = 0;
  int cap[12] = {8, 8, 8, 8, tune("C2", 8), tune("C2", 8), 8, tune("C3", 8), 8, tune("C4", 8), tune("C4", 8), 8};
  int lastk[2] = {-1, -1}, laste[2] = {0, 0};
  int tail = 0, cnt[3] = {0, 0, 0}, owner[RING_U], big = 0, lastlc = -1;
  Sched(Params& p) : P(p) { P.nseg = 0; for (int u = 0; u < RING_U; u++) owner[u] = -1; }
  void add(int kind, int k0, int n, int dep, int pre, int post, int fl, int ks = 1, int x = 0) {
    if (n <= 0) return;
    static const int size[12] = {5, 5, 3, 3, 3, 3, 4, 4, 6, 3, 3, 4};
    const int sz = size[kind], sh = kind == K_G4S, w = (kind < K_G3S ? kind : kind - 1) & 1, set = sh ? 2 : w;
    const int lc = kind < K_G2 ? 1 : big * 2, lim = RING_LIM(lc), pad = lc != lastlc;
    lastlc = lc;
    if (tune("ALN", 1)) pos = (pos + sz - 1) / sz * sz;
    if (pos + sz > lim) pos = 0;
    for (int v = 0; v < 2; v++)
      if (sh || v == w) {
        const int last = ((fl >> (2 + v)) & 1) | (fl >> 4), drain = ((fl >> v) & 1) | ((fl >> (2 + v)) & 1);
        const int pr = sh && !v ? 0 : pre, po = sh && v ? 0 : post;
        if (nr[v] && lastk[v] == kind && laste[v] == e && !pad && !pr && !(x & (v ? 19 : 3)) && !(P.run[v][nr[v] - 1] & 0x11f80000u) && !tune("NOMERGE", 0)) {
          P.run[v][nr[v] - 1] += n | po << 19 | drain << 23 | last << 24;
          laste[v] = e + n;
          continue;
        }
        lastk[v] = kind; laste[v] = e + n;
        P.run[v][nr[v]++] = n | pos << 6 | (e & 7) << 11 | sh << 14 | (sh && !v ? 0 : pre) << 15 | (sh && v ? 0 : post) << 19 | drain << 23 | last << 24 |
                            lc << 25 | (v ? x >> 4 : 0) << 28;
      }
    int i0 = 0;
    const uint32_t px = P.nseg ? P.seg[P.nseg - 1].x : ~0u;
    if (!pad && P.nseg && (int)(px & 15) == kind && !dep && (int)((px >> 16) & 1) == ks - 1 && (int)(((px >> 4) & 63) + ((px >> 10) & 63) * ks) == k0) {
      i0 = (px >> 10) & 63;
      P.seg[P.nseg - 1].x += n << 10;
    } else P.seg[P.nseg++] = make_uint2(kind | k0 << 4 | n << 10 | (ks - 1) << 16 | dep << 17 | pos << 22 | l << 27 | lc << 29, (cnt[set] & 7) << 29);
    for (int i = i0; i < i0 + n; i++) {
      int need = e - cap[kind];
      for (int u = pos; u < pos + sz; u++) { if (owner[u] > need) need = owner[u]; owner[u] = e; }
      int nw = need + 1 > tail ? need + 1 - tail : 0;
      if (i >= 14 && nw == 0) nw = 1;
      if (nw > 3 || (i >= 14 && nw != 1)) P.nseg = -1000000;
      if (i < 14) P.seg[P.nseg - 1].y |= nw << (2 * i);
      tail += nw;
      e++;
      pos += sz;
      if (i + 1 < i0 + n && pos + sz > lim) pos = 0;
    }
    cnt[set] += n;
  }
};

static void build_schedule(Params& P) {
  Sched s(P);
  for (int t0 = 0; t0 < 66; t0++) {
    const int g8 = t0 >> 2, mq = g8 >> 2, jq = (mq & 1) ? 3 - (g8 & 3) : (g8 & 3), emu = tune("MAP", 0);
    P.pair[0][t0] = t0 < 64 ? (mq * 4 + (t0 & 3)) * 8 + jq * 2 : -2;
    int t = t0;
    if (emu && t >= 60 && t != 62 && t != 65) t = t < 62 ? t + 3 : t - 3;
    const int g = t < 32 ? t & 7 : t < 60 ? 1 + (t - 32) % 7 : 0, p = t < 32 ? t >> 3 : t < 60 ? 4 + (t - 32) / 7 : t - 58;
    const int q = ((emu == 1 ? 0x64752310 : 0x75642310) >> (g * 4)) & 7, cp = p % 3;
    P.pair[1][t0] = t == 60 || t == 61 ? -2 : ((q >> 1) * 4 + (cp == 2 ? 3 : p / 3)) * 8 + (q & 1) * 4 + (cp == 2 ? p / 3 : cp) * 2;
  }
  P.u1d = tune("U1D", 200);
  P.ef[0] = tune("EFW", 0);
  P.ef[1] = tune("EFA", 0);
  P.rsd = tune("RSD", 500);
  P.ild = tune("ILD", 0);
  P.u0d = tune("U0D", 500);
  P.sud = tune("SUD", 500);
  P.pre = tune("PRE", 250);
  const int sk4 = tune("SK4", 6);
  for (int l = 0; l < 2; l++) {
    s.l = l;
    const int b = l * 16, a4 = l ? tune("PA4L", 0) : PA4;
    s.add(K_G1, 0, 16 - NT, l ? E_X : 0, 0, 0, 16);
    s.add(K_G1, 16 - NT, NT, 0, 0, 1, 0);
    s.add(K_G1 + 1, 0, PA1, l ? E_X + 1 : 0, 1, 0, 3);
    s.add(K_G1 + 1, PA1, PX - PA1, 0, 3, 0, 3);
    s.add(K_G2, 0, 16, b + E_O, 0, 1, 12);
    s.add(K_G1 + 1, PX, 16 - NT - PX, 0, 1, 0, 16);
    s.add(K_G1 + 1, 16 - NT, NT, 0, 0, PB1 ? 2 : 0, 0);
    s.add(K_G3, 0, PB1, b + E_H, 2, 0, 3);
    s.add(K_G3, PB1, PY - PB1, PB1 ? 0 : b + E_H, 4, 0, 3);
    s.add(K_G2 + 1, 0, 16, b + E_O + 1, 0, 2, 12);
    s.big = tune("BIG", 1);
    s.add(K_G3, PY, 16 - PY, 0, 2, 0, 3);
    const int pv = PV, pw = tune("PW", 0);
    s.add(K_G3 + 1, 0, PZ, 0, 0, 0, 3);
    s.add(K_G3, 16, pv, b + E_H + 1, 0, pv == 16, pv == 16 ? 12 : 3);
    s.add(K_G3 + 1, PZ, pv == 16 ? 0 : pw, 0, 0, 0, 3);
    s.add(K_G3, 16 + pv, 16 - pv, 0, 0, 1, 12);
    s.add(K_G3 + 1, PZ + (pv == 16 ? 0 : pw), 32 - PZ - (pv == 16 ? 0 : pw), 0, 1, 0, 12);
    const int k4 = l ? tune("SK4L", 5) : sk4;
    s.add(K_G4S, 0, 6, b + E_UA, 0, 0, 0, 2, 16);
    s.add(K_G4S, 12, 10, 0, 0, 0, 0, 2);
    s.add(K_G4S, 1, 16, b + E_UB, 0, 0, a4 ? 2 : 0, 2);
    s.add(K_G4, 32, a4, b + E_U1, 0, 0, 0);
    s.add(K_G4S, 32 + a4, 17 - a4, a4 ? 0 : b + E_U1, 0, 0, 0);
    if (l == 0) s.big = 0;
    s.add(K_G4S, 49, 7 - k4, 0, 0, 0, k4 ? 2 : a4 ? 4 : 12);
    s.add(K_G4S, 56 - k4, k4, 0, 1, 1, a4 ? 4 : 12);
    s.add(K_G4 + 1, 32, a4, 0, 0, 0, 12);
  }
  P.seg[0].x = P.seg[0].x + (5 << 4) - (5 << 10);
  P.seg[0].y = 0x05555555u | 5u << 29;
}

extern "C" void kernel_launch(void* const* d_in, const int* in_sizes, int n_in, void* d_out, int out_size) {
  const bf16* x = (const bf16*)d_in[0];
  const bf16* wqkv = (const bf16*)d_in[1];
  const bf16* wo = (const bf16*)d_in[2];
  const bf16* w1 = (const bf16*)d_in[4];
  const bf16* b1 = (const bf16*)d_in[5];
  const bf16* w2 = (const bf16*)d_in[6];
  const bf16* b2 = (const bf16*)d_in[7];
  bf16* out = (bf16*)d_out;

  if (!g_encode) {
    void* fn = nullptr;
    cudaDriverEntryPointQueryResult st;
    cudaGetDriverEntryPoint("cuTensorMapEncodeTiled", &fn, cudaEnableDefault, &st);
    g_encode = (PFN_encodeTiled)fn;
  }
  bf16 *h, *o, *u, *x2;
  cudaGetSymbolAddress((void**)&h, g_h);
  cudaGetSymbolAddress((void**)&o, g_o);
  cudaGetSymbolAddress((void**)&u, g_u);
  cudaGetSymbolAddress((void**)&x2, g_x2);
  Params P;
  P.xq[0] = make_map5(x, D_DIM, 32, 2, 32, 1, 2 * D_DIM, D_DIM, 64 * D_DIM, 64, 32, 2, 2, 1);
  P.xq[1] = make_map5(x2, D_DIM, 32, 2, 32, 1, 2 * D_DIM, D_DIM, 64 * D_DIM, 64, 32, 2, 2, 1);
  P.wqkv = make_map(wqkv, D_DIM, 3 * D_DIM, 64, 3, 1024);
  P.o_k = make_map(o, S_LEN, D_DIM, 64);
  P.wo = make_map_perm(wo, D_DIM, D_DIM);
  P.h_m = make_map(h, S_LEN, D_DIM, 64, 2);
  P.h_1 = make_map(h, S_LEN, D_DIM, 64);
  P.w1a = make_map(w1, S_LEN, F_DIM, 64, 2);
  P.w1b = make_map(w1, S_LEN, F_DIM, 64, 3);
  P.w2 = make_map_perm(w2, F_DIM, S_LEN);
  P.u_k = make_map(u, D_DIM, F_DIM, 128);
  build_schedule(P);
  cudaFuncSetAttribute(mega_kernel, cudaFuncAttributeMaxDynamicSharedMemorySize, SMEM_TOTAL);
  int sms = 0;
  cudaDeviceGetAttribute(&sms, cudaDevAttrMultiProcessorCount, 0);
  mega_kernel<<<sms == 132 && tune("G132", 1) ? 132 : NCTA, 384, SMEM_TOTAL, cudaStreamPerThread>>>(P, x, wqkv, b1, b2, out);
}
```
